```python
import torch

def _softmax(x, axis=-1):
    return torch.softmax(x, dim=axis)

def _gelu(x):
    return torch.nn.functional.gelu(x, approximate='tanh')

def _silu(x):
    return torch.nn.functional.silu(x)

def _sigmoid(x):
    return torch.sigmoid(x)

def _layernorm(x, axis=-1, eps=1e-05):
    m = x.mean(dim=axis, keepdim=True)
    v = x.var(dim=axis, keepdim=True, unbiased=False)
    return (x - m) / torch.sqrt(v + eps)

def _scatter_add(tgt, idx, src, axis=0):
    return tgt.clone().index_add_(axis, idx, src)

def _segment_sum(src, seg, n):
    out = torch.zeros((n,) + src.shape[1:], dtype=src.dtype)
    return out.index_add_(0, seg, src)

def _pad(x, pw):
    flat = tuple((v for pair in reversed(pw) for v in pair))
    return torch.nn.functional.pad(x, flat)
kernel_name = 'concat_heads__ssm_conv_s4__memory_aug_recurrent_mem_tr__prompt'

def setup_inputs():

    _w = lambda a: (lambda t: t.to(torch.bfloat16) if t.is_floating_point() else t)(torch.as_tensor(a))

    def _A_setup():
        B, L, D, N = (1, 2048, 512, 128)
        A_re = -(lambda _x: torch.exp(torch.as_tensor(_x)))((lambda *s: torch.randn(*s, dtype=torch.bfloat16) * 3.2)(D, N))
        A_im = torch.pi * (lambda *s: torch.randn(*s, dtype=torch.bfloat16) * 0.05)(D, N)
        B_re = (lambda *s: torch.randn(*s, dtype=torch.bfloat16) * 0.2)(D, N)
        B_im = (lambda *s: torch.randn(*s, dtype=torch.bfloat16) * 0.2)(D, N)
        C_re = (lambda *s: torch.randn(*s, dtype=torch.bfloat16) * 0.2)(D, N)
        C_im = (lambda *s: torch.randn(*s, dtype=torch.bfloat16) * 0.2)(D, N)
        log_dt = (lambda *s: torch.randn(*s, dtype=torch.bfloat16) * 0.05)(D) * 0.5 - 4.0
        Dskip = (lambda *s: torch.randn(*s, dtype=torch.bfloat16) * 0.05)(D)
        return {'u': _w((lambda *s: torch.randn(*s, dtype=torch.bfloat16) * 0.05)(B, L, D)), 'A_re': _w(A_re), 'A_im': _w(A_im), 'B_re': _w(B_re), 'B_im': _w(B_im), 'C_re': _w(C_re), 'C_im': _w(C_im), 'log_dt': _w(log_dt), 'Dskip': _w(Dskip)}
    _A_in = _A_setup()

    def _B_setup():
        B, S, Dm = (1, 2048, 512)
        H, Dh = (32, 128)
        M, seg = (8, 32)
        seg = min(seg, S)
        S = S // seg * seg
        return {'x': _w((lambda *s: torch.randn(*s, dtype=torch.bfloat16) * 0.05)(B, S, Dm)), 'mem0': _w((lambda *s: torch.randn(*s, dtype=torch.bfloat16) * 0.4)(B, M, Dm)), 'Wq': _w((lambda *s: torch.randn(*s, dtype=torch.bfloat16) * 6.4)(Dm, H, Dh) * Dm ** (-0.5)), 'Wk': _w((lambda *s: torch.randn(*s, dtype=torch.bfloat16) * 6.4)(Dm, H, Dh) * Dm ** (-0.5)), 'Wv': _w((lambda *s: torch.randn(*s, dtype=torch.bfloat16) * 0.4)(Dm, H, Dh) * Dm ** (-0.5)), 'Wo': _w((lambda *s: torch.randn(*s, dtype=torch.bfloat16) * 0.4)(H, Dh, Dm) * (H * Dh) ** (-0.5)), 'seg_len': seg}
    _B_in = _B_setup()
    return {'A_u': _A_in['u'], 'A_A_re': _A_in['A_re'], 'A_A_im': _A_in['A_im'], 'A_B_re': _A_in['B_re'], 'A_B_im': _A_in['B_im'], 'A_C_re': _A_in['C_re'], 'A_C_im': _A_in['C_im'], 'A_log_dt': _A_in['log_dt'], 'A_Dskip': _A_in['Dskip'], 'B_x': _B_in['x'], 'B_mem0': _B_in['mem0'], 'B_Wq': _B_in['Wq'], 'B_Wk': _B_in['Wk'], 'B_Wv': _B_in['Wv'], 'B_Wo': _B_in['Wo'], 'B_seg_len': _B_in['seg_len']}

def reference(A_u, A_A_re, A_A_im, A_B_re, A_B_im, A_C_re, A_C_im, A_log_dt, A_Dskip, B_x, B_mem0, B_Wq, B_Wk, B_Wv, B_Wo, B_seg_len):

    def _A_ref(u, A_re, A_im, B_re, B_im, C_re, C_im, log_dt, Dskip):
        Bsz, L, D = u.shape
        dt = torch.exp(log_dt)[:, None]
        A = A_re + 1j * A_im
        Bc = B_re + 1j * B_im
        Cc = C_re + 1j * C_im
        logdA = dt * A
        dB = dt * Bc
        l = (lambda x, dt: x.to(dt))(torch.arange(L), A_re.dtype)
        P = torch.exp(logdA[:, :, None] * l[None, None, :])
        K = torch.einsum('dn,dnl,dn->dl', Cc, P, dB).real
        L2 = 2 * L
        Kp = _pad(K, ((0, 0), (0, L)))
        up = (lambda x, *d: x.permute(*d))(u, 0, 2, 1)
        up = _pad(up, ((0, 0), (0, 0), (0, L)))
        Kf = (lambda x, axes=(-2, -1): torch.fft.rfft2(x.float(), dim=axes))(Kp[:, None, :], axes=(-2, -1))
        Uf = (lambda x, axes=(-2, -1): torch.fft.rfft2(x.float(), dim=axes))(up[:, :, None, :], axes=(-2, -1))
        Yf = Uf * Kf[None, :, :, :]
        y = (lambda x, s, axes=(-2, -1): torch.fft.irfft2(x, s=s, dim=axes).to(torch.bfloat16))(Yf, (1, L2), axes=(-2, -1))[:, :, 0, :L]
        y = (lambda x, *d: x.permute(*d))(y, 0, 2, 1) + u * Dskip[None, None, :]
        return y

    def _B_ref(x, mem0, Wq, Wk, Wv, Wo, seg_len):
        B, S, Dm = x.shape
        H, Dh = (Wq.shape[1], Wq.shape[2])
        M = mem0.shape[1]
        scale = Dh ** (-0.5)
        n_seg = S // seg_len
        L = M + seg_len
        idx = torch.arange(L)
        mask = (idx[:, None] < M) | (idx[:, None] >= idx[None, :])
        mem = mem0
        outs = []
        for s in range(n_seg):
            xs = x[:, s * seg_len:(s + 1) * seg_len, :].clone()
            h = torch.concatenate([mem, xs], axis=1)
            q = torch.einsum('btd,dhe->bhte', h, Wq)
            k = torch.einsum('btd,dhe->bhte', h, Wk)
            v = torch.einsum('btd,dhe->bhte', h, Wv)
            scores = torch.einsum('bhqe,bhke->bhqk', q, k) * scale
            scores = torch.where(mask[None, None], scores, -1000000000.0)
            p = _softmax(scores, axis=-1)
            o = torch.einsum('bhqk,bhke->bhqe', p, v)
            o = torch.einsum('bhte,hed->btd', o, Wo)
            mem = o[:, :M, :].clone()
            outs.append(o[:, M:, :])
        return torch.concatenate(outs, axis=1)
    a = _A_ref(A_u, A_A_re, A_A_im, A_B_re, A_B_im, A_C_re, A_C_im, A_log_dt, A_Dskip)
    b = _B_ref(B_x, B_mem0, B_Wq, B_Wk, B_Wv, B_Wo, B_seg_len)
    return torch.concatenate([a, b], axis=-1)
```

```cpp
#define VSTART 5
#define SPLIT_A 16
#define CHAIN_DELAY 12
#define CHAIN_ADAPT 0
struct ConvArgs { const bf16 *u,*Are,*Aim,*Bre,*Bim,*Cre,*Cim,*logdt,*Dskip; bf16* out; float* dbgK; };
#define NCONV_TASKS 64
#define CV_KP   0
#define CV_KPW  8448
#define CV_U    (8*CV_KPW)
#define CV_UW   5616
#define CV_KT   (CV_U+8*CV_UW)
#define CV_KTW  2576
#define CV_Y    (CV_KT+8*CV_KTW)
#define CV_END  (CV_Y+32768)
DEVI void cexp(float re, float im, float& zr, float& zi){
  float m=ex2(re*1.4426950408889634f);
  float r=im*0.15915494309189535f; r-=rintf(r); r*=6.283185307179586f;
  zr=m*__cosf(r); zi=m*__sinf(r);
}
DEVI void csq(float& zr, float& zi){ float a=zr*zr-zi*zi, b=2.f*zr*zi; zr=a; zi=b; }
template<int NT, bool FIRST>
DEVI void conv_delta(float (&acc)[4][4][4], unsigned (&r)[15], unsigned ub, int delta, bool diag){
  #pragma unroll
  for(int jn=4-NT;jn<4;jn++){
    unsigned b[8]; const unsigned a=ub+(8*jn-delta)*144;
    ldsm4(a,b[0],b[1],b[2],b[3]); ldsm4(a+64,b[4],b[5],b[6],b[7]);
    #pragma unroll
    for(int kk=0;kk<4;kk++)
    #pragma unroll
    for(int i=0;i<4;i++){ if(FIRST && i<kk){ if(diag) continue; }
      const int u=7+2*(i-kk);
      mma16816(acc[i][jn],r[u],r[u+1],r[u-1],r[u],b[2*kk],b[2*kk+1]); }
  }
}
template<int NT, bool FIRST>
DEVI void conv_phase(float (&acc)[4][4][4], unsigned (&r)[15], unsigned kb, unsigned ub, int d0){
  #pragma unroll 1
  for(int delta=d0;delta<d0+8;delta++){
    #pragma unroll
    for(int i=0;i<7;i++) r[i]=r[i+8];
    #pragma unroll
    for(int i=7;i<15;i++) r[i]=lds32(kb+(8*delta-7+i)*32);
    conv_delta<NT,FIRST>(acc,r,ub,delta,delta==0);
  }
}
DEVI void conv_task(const ConvArgs& ca, unsigned sb, int task, int w, int lane){
  const int d0=task*8, d=d0+w, tid=w*32+lane, g=lane>>2, t=lane&3;
  for(int i=tid;i<8*7*9;i+=256){ int c=i/63, rem=i%63; sts128(sb+CV_U+c*CV_UW+(rem/9)*144+(rem%9)*16,0,0,0,0); }
  #pragma unroll 2
  for(int i=0;i<8;i++){ const int tt=tid+256*i; uint4 v=__ldg((const uint4*)(ca.u+(size_t)tt*512+d0)); unsigned q[4]={v.x,v.y,v.z,v.w};
    const unsigned o=sb+CV_U+((tt>>6)+7)*144+(tt&63)*2;
    #pragma unroll
    for(int c=0;c<4;c++){ asm volatile("st.shared.u16 [%0],%1;"::"r"(o+(2*c)*CV_UW),"h"((unsigned short)(q[c]&0xffff)):"memory"); asm volatile("st.shared.u16 [%0],%1;"::"r"(o+(2*c+1)*CV_UW),"h"((unsigned short)(q[c]>>16)):"memory"); } }
  const float dt=__bfloat162float(__float2bfloat16(expf(__bfloat162float(ca.logdt[d]))));
  float c0[4]={0,0,0,0},c0b[4]={0,0,0,0},c1[4]={0,0,0,0},c2[4]={0,0,0,0},c3[4]={0,0,0,0}; float klast=0.f;
  #pragma unroll 1
  for(int ks=0;ks<16;ks++){
    float yr[2][2],yi[2][2],er[2][2],ei[2][2],cbr[2],cbi[2];
    #pragma unroll
    for(int q=0;q<2;q++){ const int n=d*128+8*ks+4*q+t;
      const float ar=dt*__bfloat162float(ca.Are[n]), ai=dt*__bfloat162float(ca.Aim[n]);
      const float br=dt*__bfloat162float(ca.Bre[n]), bi=dt*__bfloat162float(ca.Bim[n]);
      const float cr=__bfloat162float(ca.Cre[n]), ci=__bfloat162float(ca.Cim[n]);
      cbr[q]=cr*br-ci*bi; cbi[q]=cr*bi+ci*br;
      cexp(ar*(float)g,ai*(float)g,yr[q][0],yi[q][0]); cexp(ar*(float)(g+8),ai*(float)(g+8),yr[q][1],yi[q][1]);
      cexp(ar*(float)(16*g),ai*(float)(16*g),er[q][0],ei[q][0]); cexp(ar*(float)(16*g+128),ai*(float)(16*g+128),er[q][1],ei[q][1]);
      float zr,zi; cexp(ar*2048.f,ai*2048.f,zr,zi); klast+=cbr[q]*zr-cbi[q]*zi; }
    #define AFR() pack2(yr[0][0],yi[0][0]),pack2(yr[0][1],yi[0][1]),pack2(yr[1][0],yi[1][0]),pack2(yr[1][1],yi[1][1])
    #define BFR(q,h) pack2(cbr[q]*er[q][h]-cbi[q]*ei[q][h], -(cbr[q]*ei[q][h]+cbi[q]*er[q][h]))
    mma16816(c0,AFR(),BFR(0,0),BFR(1,0));
    mma16816(c0b,AFR(),BFR(0,1),BFR(1,1));
    #define SQ() { csq(yr[0][0],yi[0][0]); csq(yr[0][1],yi[0][1]); csq(yr[1][0],yi[1][0]); csq(yr[1][1],yi[1][1]); csq(er[0][1],ei[0][1]); csq(er[1][1],ei[1][1]); }
    SQ(); mma16816(c1,AFR(),BFR(0,1),BFR(1,1));
    SQ(); mma16816(c2,AFR(),BFR(0,1),BFR(1,1));
    SQ(); mma16816(c3,AFR(),BFR(0,1),BFR(1,1));
  }
  klast+=__shfl_xor_sync(~0u,klast,1); klast+=__shfl_xor_sync(~0u,klast,2);
  { const unsigned kt=sb+CV_KT+w*CV_KTW;
    #define PUT(base,c) { sts32(kt+((base)+16*(2*t)+g)*4,__float_as_uint(c[0])); sts32(kt+((base)+16*(2*t+1)+g)*4,__float_as_uint(c[1])); sts32(kt+((base)+16*(2*t)+g+8)*4,__float_as_uint(c[2])); sts32(kt+((base)+16*(2*t+1)+g+8)*4,__float_as_uint(c[3])); }
    PUT(0,c0); PUT(128,c0b); PUT(256,c1); PUT(384,c2); PUT(512,c3);
    if(lane==0) sts32(kt+640*4,__float_as_uint(klast));
    __syncwarp();
    const unsigned kp=sb+CV_KP+w*CV_KPW;
    float carry=0.f;
    #pragma unroll 1
    for(int x0=-64;x0<2048;x0+=32){ const int x=x0+lane; float kv=0.f;
      if(x>=0){ const int lr=(int)__bfloat162float(__float2bfloat16((float)x)); int idx;
        if(lr<256) idx=lr; else { const int k=(31-__clz(lr))-7; idx= lr==2048? 640 : 256+(k-1)*128+((lr>>k)-128); }
        kv=__uint_as_float(lds32(kt+idx*4)); if(ca.dbgK) ca.dbgK[d*2048+x]=kv; }
      float km1=__shfl_up_sync(~0u,kv,1); if(lane==0) km1=carry; carry=__shfl_sync(~0u,kv,31);
      sts32(kp+(x+64)*4,pack2(kv,km1)); }
  }
  bar_sync(11,256);
  float acc[4][4][4];
  #pragma unroll
  for(int i=0;i<4;i++)
  #pragma unroll
  for(int j=0;j<4;j++){ acc[i][j][0]=acc[i][j][1]=acc[i][j][2]=acc[i][j][3]=0.f; }
  const unsigned kb=sb+CV_KP+w*CV_KPW+(64+g-2*t)*4;
  const unsigned ub=sb+CV_U+w*CV_UW+((lane&7)+7)*144+(lane>>3)*16;
  unsigned r[15];
  #pragma unroll
  for(int i=8;i<15;i++) r[i]=lds32(kb+(i-15)*32);
  conv_phase<4,true>(acc,r,kb,ub,0);
  conv_phase<3,false>(acc,r,kb,ub,8);
  conv_phase<2,false>(acc,r,kb,ub,16);
  conv_phase<1,false>(acc,r,kb,ub,24);
  #pragma unroll
  for(int i=0;i<4;i++)
  #pragma unroll
  for(int j=0;j<4;j++)
  #pragma unroll
  for(int e=0;e<4;e++){ const int b=16*i+g+8*(e>>1), a=8*j+2*t+(e&1); bf16 v=__float2bfloat16(acc[i][j][e]);
    asm volatile("st.shared.u16 [%0],%1;"::"r"(sb+CV_Y+(a*64+b)*16+w*2),"h"(*(unsigned short*)&v):"memory"); }
  bar_sync(11,256);
  { uint4 dv=__ldg((const uint4*)(ca.Dskip+d0)); const unsigned dq[4]={dv.x,dv.y,dv.z,dv.w};
    #pragma unroll 2
    for(int i=0;i<8;i++){ const int tt=tid+256*i; uint4 uv=__ldg((const uint4*)(ca.u+(size_t)tt*512+d0)); uint4 yv=lds128(sb+CV_Y+tt*16);
      const unsigned uq[4]={uv.x,uv.y,uv.z,uv.w}, yq[4]={yv.x,yv.y,yv.z,yv.w}; unsigned o[4];
      #pragma unroll
      for(int c=0;c<4;c++){ unsigned s=pack2(blo(uq[c])*blo(dq[c]),bhi(uq[c])*bhi(dq[c])); o[c]=pack2(blo(yq[c])+blo(s),bhi(yq[c])+bhi(s)); }
      *(uint4*)(ca.out+(size_t)tt*1024+d0)=make_uint4(o[0],o[1],o[2],o[3]); } }
}
__device__ __align__(1024) bf16 g_o[2048*4096];
__device__ __align__(1024) float g_part[4*4*8*128*128];
__device__ unsigned g_oflag[16*32];
__device__ unsigned g_pcnt[16*4];
struct WorkMaps { CUtensorMap x, wq, wk, wv, wo, o, o64, out64; };
struct WorkArgs { bf16* out; int nw; };
#define WS_STAGE 0
#define WS_KX    131072
#define WS_VX    163840
#define WS_KM    196608
#define WS_VM    204800
#define WS_BAR   212992
#define WS_END   (WS_BAR+256)
enum { TK_KV=0, TK_CONV=1, TK_ATT=2, TK_WO=3, TK_END=4 };
struct Task { int type, m, n, ks, nsplit; };
DEVI int t3_nsplit(int m){ return m<12?1:(m<14?2:(m==14?4:8)); }
struct TaskIter {
  int wk,nw,phase,i;
  DEVI void init(int wk_,int nw_){ wk=wk_; nw=nw_; phase=0; i=wk_; }
  DEVI Task next(){
    Task t; t.ks=0; t.nsplit=1; t.m=0; t.n=0;
    if(phase==0){ if(i<1024){ t.type=TK_KV; t.m=i>>6; t.n=i&63; i+=nw; return t; } phase=1; i=wk; }
    if(phase==1){ if(i<NCONV_TASKS){ t.type=TK_CONV; t.n=i; i+=nw; return t; } phase=2; i=wk; }
    int j=i;
    for(int m=0;m<=16;m++){
      if(m<16){ if(j<32){ t.type=TK_ATT; t.m=m; t.n=j; i+=nw; return t; } j-=32; }
      if(m>=1){ int ns=t3_nsplit(m-1); int c=4*ns; if(j<c){ t.type=TK_WO; t.m=m-1; t.n=j/ns; t.ks=j%ns; t.nsplit=ns; i+=nw; return t; } j-=c; }
    }
    t.type=TK_END; return t;
  }
};
DEVI void wait_flag(const unsigned* p, unsigned tgt){ int g=0; while((int)(ldg_acquire(p)-tgt)<0 && ++g<WAIT_LIMIT){ __nanosleep(64);} }

DEVI void worker_producer(const WorkMaps& mp, unsigned sb, int wk, int nw, unsigned epoch){
  TaskIter it; it.init(wk,nw); unsigned st=0, ph=1, ntask=0; bool prevconv=false;
  const unsigned B=sb+WS_BAR;
  for(;;){ Task t=it.next(); if(t.type==TK_END) break;
    if(t.type==TK_CONV){ if(ntask>0) mbar_wait(B+80,(ntask-1)&1); prevconv=true; ntask++; continue; }
    if(prevconv || t.type==TK_ATT){ if(ntask>0) mbar_wait(B+80,(ntask-1)&1); prevconv=false; }
    if(t.type==TK_ATT){
      wait_flag(&g_kvflag[t.m*32+t.n],epoch*2);
      asm volatile("fence.proxy.async.global;":::"memory");
      mbar_expect(B+64,65536);
      for(int sg=0;sg<4;sg++) for(int eh=0;eh<2;eh++){ size_t off=((size_t)(t.m*4+sg)*32+t.n)*8192+eh*4096;
        bulk_g2s(sb+WS_KX+eh*16384+sg*4096,g_kx+off,4096,B+64); bulk_g2s(sb+WS_VX+eh*16384+sg*4096,g_vx+off,4096,B+64); }
    }
    const int nkb = t.type==TK_WO ? 64/t.nsplit : 8; const int kb0 = t.type==TK_WO ? t.ks*nkb : 0;
    for(int kb=kb0;kb<kb0+nkb;kb++){
      if(t.type==TK_WO && (kb&1)==0){ wait_flag(&g_oflag[t.m*32+(kb>>1)],epoch); asm volatile("fence.proxy.async.global;":::"memory"); }
      mbar_wait(B+32+st*8,ph);
      const unsigned full=B+st*8, sa=sb+WS_STAGE+st*32768;
      mbar_expect(full,32768);
      if(t.type==TK_WO){ tma_load2d(sa,&mp.o,kb*64,t.m*128,full); tma_load2d(sa+16384,&mp.wo,t.n*128,kb*64,full); tma_load2d(sa+24576,&mp.wo,t.n*128+64,kb*64,full); }
      else { const CUtensorMap* w= t.type==TK_ATT? &mp.wq : (t.n<32? &mp.wk : &mp.wv); const int col=(t.n&31)*128;
        tma_load2d(sa,&mp.x,kb*64,t.m*128,full); tma_load2d(sa+16384,w,col,kb*64,full); tma_load2d(sa+24576,w,col+64,kb*64,full); }
      if(++st==4){ st=0; ph^=1; }
    }
    if(t.type==TK_ATT){
      for(int sg=0;sg<4;sg++) wait_flag(&g_mflag[(t.m*4+sg)*32+t.n],epoch*2);
      asm volatile("fence.proxy.async.global;":::"memory");
      mbar_expect(B+72,16384);
      for(int sg=0;sg<4;sg++) for(int eh=0;eh<2;eh++){ size_t off=((size_t)(t.m*4+sg)*32+t.n)*2048+eh*1024;
        bulk_g2s(sb+WS_KM+eh*4096+sg*1024,g_km+off,1024,B+72); bulk_g2s(sb+WS_VM+eh*4096+sg*1024,g_vm+off,1024,B+72); }
    }
    ntask++;
  }
}
DEVI void worker_storer(const WorkMaps& mp, unsigned sb, int wk, int nw, unsigned epoch, int lane){
  TaskIter it; it.init(wk,nw); const unsigned B=sb+WS_BAR;
  for(;;){ Task t=it.next(); if(t.type==TK_END) break;
    bar_sync(10,288);
    if(lane==0){
      if(t.type==TK_KV){ unsigned char* g=(t.n<32? g_kx: g_vx);
        for(int sg=0;sg<4;sg++) bulk_s2g(g+((size_t)(t.m*4+sg)*32+(t.n&31))*8192, sb+WS_KX+sg*8192, 8192);
      } else if(t.type==TK_ATT){
        for(int r=0;r<2;r++) for(int eh=0;eh<2;eh++) tma_store2d(&mp.o64,sb+WS_KX+eh*16384+r*8192,t.n*128+eh*64,t.m*128+r*64);
      } else if(t.type==TK_WO && t.nsplit==1){
        for(int r=0;r<2;r++) for(int eh=0;eh<2;eh++) tma_store2d(&mp.out64,sb+WS_KX+eh*16384+r*8192,512+t.n*128+eh*64,t.m*128+r*64);
      }
      asm volatile("cp.async.bulk.commit_group;":::"memory");
      asm volatile("cp.async.bulk.wait_group.read 0;":::"memory");
      mbar_arrive(B+80);
      asm volatile("cp.async.bulk.wait_group 0;":::"memory");
      if(t.type==TK_KV) red_release_add(&g_kvflag[t.m*32+(t.n&31)],1);
      else if(t.type==TK_ATT) stg_release(&g_oflag[t.m*32+t.n],epoch);
    }
    __syncwarp();
  }
}
DEVI void stage_tile(const float* acc, unsigned base, unsigned ehstride, int wi, int lane){
  const int row=16*wi+(lane&7)+8*((lane>>3)&1);
  #pragma unroll
  for(int jp=0;jp<8;jp++){ const int j=2*jp; const int eh=j>>3, c=(j&7)+(lane>>4);
    stsm4(base+eh*ehstride+row*128+((c^(row&7))<<4), pack2(acc[4*j],acc[4*j+1]), pack2(acc[4*j+2],acc[4*j+3]), pack2(acc[4*j+4],acc[4*j+5]), pack2(acc[4*j+6],acc[4*j+7])); }
}
DEVI void worker_consumer(const WorkArgs& wa, const ConvArgs& ca, unsigned sb, int wk, int nw, unsigned epoch, int w, int lane){
  TaskIter it; it.init(wk,nw); unsigned st=0, ph=0, natt=0, ntask=0; const unsigned B=sb+WS_BAR;
  const int r=w>>2, wi=w&3, g=lane>>2, tq=lane&3;
  for(;;){ Task t=it.next(); if(t.type==TK_END) break;
    if(t.type==TK_CONV){ if(ntask>0) mbar_wait(B+80,(ntask-1)&1); conv_task(ca,sb,t.n,w,lane); asm volatile("fence.proxy.async.shared::cta;":::"memory"); bar_sync(10,288); ntask++; continue; }
    float acc[64];
    const int nkb = t.type==TK_WO ? 64/t.nsplit : 8;
    for(int kb=0;kb<nkb;kb++){
      mbar_wait(B+st*8,ph);
      const unsigned sa=sb+WS_STAGE+st*32768;
      const uint64_t da=mkdesc(sa+r*8192,16,1024), db=mkdesc(sa+16384,8192,1024);
      wg_fence();
      #pragma unroll
      for(int k=0;k<4;k++) wg_ss_n128_tb(acc,da+k*2,db+k*128,(kb|k)!=0);
      wg_commit();
      if(kb>0){ wg_wait<1>(); if(lane==0) mbar_arrive(B+32+((st+3)&3)*8); }
      if(++st==4){ st=0; ph^=1; }
    }
    wg_wait<0>(); if(lane==0) mbar_arrive(B+32+((st+3)&3)*8);
    if(t.type!=TK_ATT && ntask>0) mbar_wait(B+80,(ntask-1)&1);
    if(t.type==TK_KV){
      const int row=16*(wi&1)+(lane&7)+8*((lane>>3)&1); const unsigned base=sb+WS_KX+(2*r+(wi>>1))*8192;
      #pragma unroll
      for(int jp=0;jp<8;jp++){ const int j=2*jp; const int eh=j>>3, c=(j&7)+(lane>>4);
        stsm4(base+eh*4096+row*128+((c^(row&7))<<4), pack2(acc[4*j],acc[4*j+1]), pack2(acc[4*j+2],acc[4*j+3]), pack2(acc[4*j+4],acc[4*j+5]), pack2(acc[4*j+6],acc[4*j+7])); }
    } else if(t.type==TK_ATT){
      unsigned qa[8][4];
      #pragma unroll
      for(int k=0;k<8;k++){ qa[k][0]=pack2(acc[8*k],acc[8*k+1]); qa[k][1]=pack2(acc[8*k+2],acc[8*k+3]); qa[k][2]=pack2(acc[8*k+4],acc[8*k+5]); qa[k][3]=pack2(acc[8*k+6],acc[8*k+7]); }
      float sx[32], sm[8];
      mbar_wait(B+64,natt&1);
      wg_fence();
      #pragma unroll
      for(int k=0;k<8;k++) wg_rs_n64(sx,qa[k][0],qa[k][1],qa[k][2],qa[k][3],mkdesc(sb+WS_KX+(k>>2)*16384+r*8192+(k&3)*32,16,1024),k!=0);
      wg_commit();
      mbar_wait(B+72,natt&1);
      #pragma unroll
      for(int k=0;k<8;k++) wg_rs_n16(sm,qa[k][0],qa[k][1],qa[k][2],qa[k][3],mkdesc(sb+WS_KM+(k>>2)*4096+r*2048+(k&3)*32,16,1024),k!=0);
      wg_commit(); wg_wait<0>();
      const bool s1=(wi>>1)!=0; float x[16], mm[4];
      #pragma unroll
      for(int i=0;i<16;i++) x[i]= s1? sx[16+i]: sx[i];
      #pragma unroll
      for(int i=0;i<4;i++) mm[i]= s1? sm[4+i]: sm[i];
      const int rho0=16*(wi&1)+g, rho1=rho0+8; const float NEG=-3.0e38f;
      #pragma unroll
      for(int j=0;j<4;j++){ const int c=8*j+2*tq;
        if(c>rho0) x[4*j]=NEG; if(c+1>rho0) x[4*j+1]=NEG; if(c>rho1) x[4*j+2]=NEG; if(c+1>rho1) x[4*j+3]=NEG; }
      float m0=fmaxf(mm[0],mm[1]), m1=fmaxf(mm[2],mm[3]);
      #pragma unroll
      for(int j=0;j<4;j++){ m0=fmaxf(m0,fmaxf(x[4*j],x[4*j+1])); m1=fmaxf(m1,fmaxf(x[4*j+2],x[4*j+3])); }
      m0=fmaxf(m0,__shfl_xor_sync(~0u,m0,1)); m0=fmaxf(m0,__shfl_xor_sync(~0u,m0,2));
      m1=fmaxf(m1,__shfl_xor_sync(~0u,m1,1)); m1=fmaxf(m1,__shfl_xor_sync(~0u,m1,2));
      const float sl2=0.08838834764831845f*1.4426950408889634f; const float n0=-m0*sl2, n1=-m1*sl2;
      unsigned px[4][2], pm[2]; float l0=0.f,l1=0.f;
      #pragma unroll
      for(int j=0;j<4;j++){ px[j][0]=pack2(ex2(fmaf(x[4*j],sl2,n0)),ex2(fmaf(x[4*j+1],sl2,n0))); px[j][1]=pack2(ex2(fmaf(x[4*j+2],sl2,n1)),ex2(fmaf(x[4*j+3],sl2,n1)));
        l0+=blo(px[j][0])+bhi(px[j][0]); l1+=blo(px[j][1])+bhi(px[j][1]); }
      pm[0]=pack2(ex2(fmaf(mm[0],sl2,n0)),ex2(fmaf(mm[1],sl2,n0))); pm[1]=pack2(ex2(fmaf(mm[2],sl2,n1)),ex2(fmaf(mm[3],sl2,n1)));
      l0+=blo(pm[0])+bhi(pm[0]); l1+=blo(pm[1])+bhi(pm[1]);
      l0+=__shfl_xor_sync(~0u,l0,1); l0+=__shfl_xor_sync(~0u,l0,2); l1+=__shfl_xor_sync(~0u,l1,1); l1+=__shfl_xor_sync(~0u,l1,2);
      wg_fence();
      #pragma unroll
      for(int kk=0;kk<4;kk++){ const bool on=((kk>>1)!=0)==s1; const int j=2*(kk&1);
        wg_rs_n128_tb(acc, on?px[j][0]:0u, on?px[j][1]:0u, on?px[j+1][0]:0u, on?px[j+1][1]:0u, mkdesc(sb+WS_VX+r*8192+kk*2048,16384,1024), kk!=0); }
      wg_rs_n128_tb(acc, s1?0u:pm[0], s1?0u:pm[1], s1?pm[0]:0u, s1?pm[1]:0u, mkdesc(sb+WS_VM+r*2048,4096,1024), 1);
      wg_commit(); wg_wait<0>();
      const float i0=__fdividef(1.f,l0), i1=__fdividef(1.f,l1);
      #pragma unroll
      for(int j=0;j<16;j++){ acc[4*j]*=i0; acc[4*j+1]*=i0; acc[4*j+2]*=i1; acc[4*j+3]*=i1; }
      stage_tile(acc,sb+WS_KX+r*8192,16384,wi,lane);
      natt++;
    } else {
      if(t.nsplit==1) stage_tile(acc,sb+WS_KX+r*8192,16384,wi,lane);
      else {
        float* pb=g_part+((size_t)((t.m-12)*4+t.n)*8)*16384;
        float* p=pb+(size_t)t.ks*16384+(r*64+16*wi+g)*128+2*tq;
        #pragma unroll
        for(int j=0;j<16;j++){ *(float2*)(p+8*j)=make_float2(acc[4*j],acc[4*j+1]); *(float2*)(p+8*128+8*j)=make_float2(acc[4*j+2],acc[4*j+3]); }
        __threadfence(); bar_sync(11,256);
        if(w==0&&lane==0){ red_release_add(&g_pcnt[t.m*4+t.n],1); wait_flag(&g_pcnt[t.m*4+t.n],epoch*t.nsplit); }
        bar_sync(11,256);
        const int rows=128/t.nsplit, tid=w*32+lane;
        for(int i=tid;i<rows*32;i+=256){ const int rr=t.ks*rows+(i>>5), c4=(i&31)*4; float4 s=make_float4(0,0,0,0);
          for(int k=0;k<t.nsplit;k++){ float4 v=__ldcg((const float4*)(pb+(size_t)k*16384+rr*128+c4)); s.x+=v.x; s.y+=v.y; s.z+=v.z; s.w+=v.w; }
          uint2 o; o.x=pack2(s.x,s.y); o.y=pack2(s.z,s.w);
          *(uint2*)(wa.out+(size_t)(t.m*128+rr)*1024+512+t.n*128+c4)=o; }
      }
    }
    asm volatile("fence.proxy.async.shared::cta;":::"memory");
    bar_sync(10,288);
    ntask++;
  }
}
struct AllArgs { ChainArgs c; ConvArgs cv; WorkArgs w; };
#define SMEM_TOTAL (CS_TOTAL>WS_END?CS_TOTAL:WS_END)
template<int DBG>
__global__ void __launch_bounds__(384,1) fused_kernel(const __grid_constant__ WorkMaps mp, const __grid_constant__ AllArgs a){
  extern __shared__ __align__(1024) unsigned char smem[];
  const unsigned sb=s2u(smem);
  const unsigned epoch=*(volatile unsigned*)&g_epoch+1;
  const int cta=blockIdx.x;
  if(cta<64){
    chain_role<DBG>(a.c,sb,cta,epoch);
  } else {
    const int tid=threadIdx.x, lane=tid&31; const int w=__shfl_sync(~0u,tid>>5,0); const int wk=cta-64, nw=gridDim.x-64;
    if(tid==0){ const unsigned B=sb+WS_BAR; for(int i=0;i<4;i++){ mbar_init(B+i*8,1); mbar_init(B+32+i*8,8);} mbar_init(B+64,1); mbar_init(B+72,1); mbar_init(B+80,1);
      asm volatile("fence.mbarrier_init.release.cluster;":::"memory"); asm volatile("fence.proxy.async.shared::cta;":::"memory"); }
    __syncthreads();
    if(w>=8){
      reg_dealloc<40>();
      if(w==8){ if(lane==0) worker_producer(mp,sb,wk,nw,epoch); }
      else if(w==9) worker_storer(mp,sb,wk,nw,epoch,lane);
    } else {
      reg_alloc<232>();
      worker_consumer(a.w,a.cv,sb,wk,nw,epoch,w,lane);
    }
  }
  __syncthreads();
  if(threadIdx.x==0){ __threadfence(); unsigned o=atomicAdd(&g_done,1); if(o==gridDim.x-1){ g_done=0; __threadfence(); *(volatile unsigned*)&g_epoch=epoch; } }
}
typedef CUresult (*EncFn)(CUtensorMap*,CUtensorMapDataType,cuuint32_t,void*,const cuuint64_t*,const cuuint64_t*,const cuuint32_t*,const cuuint32_t*,CUtensorMapInterleave,CUtensorMapSwizzle,CUtensorMapL2promotion,CUtensorMapFloatOOBfill);
static void mkmap(EncFn enc, CUtensorMap* m, const void* p, uint64_t cols, uint64_t rows, uint32_t bc, uint32_t br){
  cuuint64_t gd[2]={cols,rows}; cuuint64_t gs[1]={cols*2}; cuuint32_t box[2]={bc,br}; cuuint32_t es[2]={1,1};
  enc(m,CU_TENSOR_MAP_DATA_TYPE_BFLOAT16,2,(void*)p,gd,gs,box,es,CU_TENSOR_MAP_INTERLEAVE_NONE,CU_TENSOR_MAP_SWIZZLE_128B,CU_TENSOR_MAP_L2_PROMOTION_L2_128B,CU_TENSOR_MAP_FLOAT_OOB_FILL_NONE);
}

extern "C" void kernel_launch(void* const* d_in, const int* in_sizes, int n_in, void* d_out, int out_size) {
  (void)in_sizes; (void)n_in; (void)out_size;
  static EncFn enc = nullptr; static int nclusters = 0; static void* go = nullptr;
  auto kern = fused_kernel<0>;
  cudaLaunchConfig_t cfg = {};
  cfg.blockDim = dim3(384); cfg.dynamicSmemBytes = SMEM_TOTAL; cfg.stream = cudaStreamPerThread;
  cudaLaunchAttribute at[1]; at[0].id = cudaLaunchAttributeClusterDimension; at[0].val.clusterDim.x = 2; at[0].val.clusterDim.y = 1; at[0].val.clusterDim.z = 1;
  cfg.attrs = at; cfg.numAttrs = 1;
  if (!enc) {
    void* fn = nullptr; cudaDriverEntryPointQueryResult qr;
    cudaGetDriverEntryPoint("cuTensorMapEncodeTiled", &fn, cudaEnableDefault, &qr);
    enc = (EncFn)fn;
    cudaFuncSetAttribute(kern, cudaFuncAttributeMaxDynamicSharedMemorySize, SMEM_TOTAL);
    cfg.gridDim = dim3(132);
    cudaOccupancyMaxActiveClusters(&nclusters, kern, &cfg);
    cudaGetSymbolAddress(&go, g_o);
  }
  AllArgs a;
  a.cv.u=(const bf16*)d_in[0]; a.cv.Are=(const bf16*)d_in[1]; a.cv.Aim=(const bf16*)d_in[2]; a.cv.Bre=(const bf16*)d_in[3]; a.cv.Bim=(const bf16*)d_in[4];
  a.cv.Cre=(const bf16*)d_in[5]; a.cv.Cim=(const bf16*)d_in[6]; a.cv.logdt=(const bf16*)d_in[7]; a.cv.Dskip=(const bf16*)d_in[8];
  a.c.x=(const bf16*)d_in[9]; a.c.mem0=(const bf16*)d_in[10]; a.c.Wq=(const bf16*)d_in[11]; a.c.Wk=(const bf16*)d_in[12]; a.c.Wv=(const bf16*)d_in[13]; a.c.Wo=(const bf16*)d_in[14];
  a.c.delay = CHAIN_DELAY; a.c.adapt = CHAIN_ADAPT; a.c.skip = 0;
  a.cv.out=(bf16*)d_out; a.cv.dbgK=nullptr; a.w.out=(bf16*)d_out;
  const int grid = 2*nclusters; a.w.nw = grid-64;
  WorkMaps mp;
  mkmap(enc,&mp.x,a.c.x,512,2048,64,128); mkmap(enc,&mp.wq,a.c.Wq,4096,512,64,64); mkmap(enc,&mp.wk,a.c.Wk,4096,512,64,64); mkmap(enc,&mp.wv,a.c.Wv,4096,512,64,64);
  mkmap(enc,&mp.wo,a.c.Wo,512,4096,64,64); mkmap(enc,&mp.o,go,4096,2048,64,128); mkmap(enc,&mp.o64,go,4096,2048,64,64); mkmap(enc,&mp.out64,d_out,1024,2048,64,64);
  cfg.gridDim = dim3(grid);
  cudaLaunchKernelEx(&cfg, kern, mp, a);
}
```

```cpp
#define VSTART 7
#define ANN 0
#define ROT 1
#define DEFN 0
#define CHAIN_DELAY 16
#include <cuda.h>
#include <cuda_runtime.h>
#include <cuda_bf16.h>
#include <stdint.h>
typedef __nv_bfloat16 bf16;
#define DEVI __device__ __forceinline__
DEVI unsigned s2u(const void* p){return (unsigned)__cvta_generic_to_shared(p);}
DEVI unsigned mapa(unsigned a, unsigned r){unsigned o; asm("mapa.shared::cluster.u32 %0,%1,%2;":"=r"(o):"r"(a),"r"(r)); return o;}
DEVI void mbar_init(unsigned mb, unsigned cnt){ asm volatile("mbarrier.init.shared::cta.b64 [%0], %1;"::"r"(mb),"r"(cnt):"memory"); }
DEVI void mbar_expect(unsigned mb, unsigned bytes){ asm volatile("mbarrier.arrive.expect_tx.shared::cta.b64 _, [%0], %1;"::"r"(mb),"r"(bytes):"memory"); }
DEVI void mbar_arrive(unsigned mb){ asm volatile("mbarrier.arrive.shared::cta.b64 _, [%0];"::"r"(mb):"memory"); }
#define WAIT_LIMIT 4000000
#define SUSPEND_NS 0
DEVI void mbar_wait(unsigned mb, unsigned ph){
  asm volatile("{.reg .pred p; .reg .u32 c; mov.u32 c,0;\n"
   "LAB_WAIT: mbarrier.try_wait.parity.shared::cta.b64 p,[%0],%1; @p bra LAB_DONE; add.u32 c,c,1; setp.lt.u32 p,c,%2; @p bra LAB_WAIT;\n"
   "LAB_DONE: }"::"r"(mb),"r"(ph),"n"(WAIT_LIMIT):"memory");
}
DEVI void bar_sync(int id, int n){ asm volatile("bar.sync %0,%1;"::"r"(id),"r"(n):"memory"); }
DEVI void bar_arrive(int id, int n){ asm volatile("bar.arrive %0,%1;"::"r"(id),"r"(n):"memory"); }
DEVI void stasync16(unsigned dst, unsigned a, unsigned b, unsigned c, unsigned d, unsigned mb){
  asm volatile("st.async.weak.shared::cluster.mbarrier::complete_tx::bytes.v4.b32 [%0],{%1,%2,%3,%4},[%5];"::"r"(dst),"r"(a),"r"(b),"r"(c),"r"(d),"r"(mb):"memory");}
DEVI void stasync4(unsigned dst, unsigned a, unsigned mb){
  asm volatile("st.async.weak.shared::cluster.mbarrier::complete_tx::bytes.b32 [%0],%1,[%2];"::"r"(dst),"r"(a),"r"(mb):"memory");}
DEVI void bulk_g2s(unsigned dst, const void* src, unsigned bytes, unsigned mb){
  asm volatile("cp.async.bulk.shared::cluster.global.mbarrier::complete_tx::bytes [%0],[%1],%2,[%3];"::"r"(dst),"l"(src),"r"(bytes),"r"(mb):"memory");}
DEVI void bulk_s2g(void* dst, unsigned src, unsigned bytes){ asm volatile("cp.async.bulk.global.shared::cta.bulk_group [%0],[%1],%2;"::"l"(dst),"r"(src),"r"(bytes):"memory");}
DEVI void cpasync16(unsigned dst, const void* src){ asm volatile("cp.async.cg.shared.global [%0],[%1],16;"::"r"(dst),"l"(src):"memory"); }
DEVI void cpasync_commit(){ asm volatile("cp.async.commit_group;":::"memory"); }
template<int N> DEVI void cpasync_wait(){ asm volatile("cp.async.wait_group %0;"::"n"(N):"memory"); }
DEVI void ldsm4(unsigned addr, unsigned& a, unsigned& b, unsigned& c, unsigned& d){
  asm volatile("ldmatrix.sync.aligned.m8n8.x4.shared.b16 {%0,%1,%2,%3},[%4];":"=r"(a),"=r"(b),"=r"(c),"=r"(d):"r"(addr):"memory");}
DEVI void ldsm4t(unsigned addr, unsigned& a, unsigned& b, unsigned& c, unsigned& d){
  asm volatile("ldmatrix.sync.aligned.m8n8.x4.trans.shared.b16 {%0,%1,%2,%3},[%4];":"=r"(a),"=r"(b),"=r"(c),"=r"(d):"r"(addr):"memory");}
DEVI unsigned movm(unsigned a){ unsigned d; asm volatile("movmatrix.sync.aligned.m8n8.trans.b16 %0,%1;":"=r"(d):"r"(a)); return d;}
DEVI void mma16816(float* c, unsigned a0,unsigned a1,unsigned a2,unsigned a3, unsigned b0, unsigned b1){
  asm volatile("mma.sync.aligned.m16n8k16.row.col.f32.bf16.bf16.f32 {%0,%1,%2,%3},{%4,%5,%6,%7},{%8,%9},{%0,%1,%2,%3};"
   :"+f"(c[0]),"+f"(c[1]),"+f"(c[2]),"+f"(c[3]):"r"(a0),"r"(a1),"r"(a2),"r"(a3),"r"(b0),"r"(b1));}
DEVI void mma1688(float* c, unsigned a0,unsigned a1, unsigned b0){
  asm volatile("mma.sync.aligned.m16n8k8.row.col.f32.bf16.bf16.f32 {%0,%1,%2,%3},{%4,%5},{%6},{%0,%1,%2,%3};"
   :"+f"(c[0]),"+f"(c[1]),"+f"(c[2]),"+f"(c[3]):"r"(a0),"r"(a1),"r"(b0));}
DEVI unsigned pack2(float lo, float hi){ unsigned d; asm("cvt.rn.bf16x2.f32 %0,%1,%2;":"=r"(d):"f"(hi),"f"(lo)); return d;}
DEVI float blo(unsigned u){ return __uint_as_float(u<<16);}
DEVI float bhi(unsigned u){ return __uint_as_float(u&0xffff0000u);}
DEVI uint4 lds128(unsigned a){ uint4 v; asm volatile("ld.shared.v4.u32 {%0,%1,%2,%3},[%4];":"=r"(v.x),"=r"(v.y),"=r"(v.z),"=r"(v.w):"r"(a):"memory"); return v;}
DEVI uint2 lds64(unsigned a){ uint2 v; asm volatile("ld.shared.v2.u32 {%0,%1},[%2];":"=r"(v.x),"=r"(v.y):"r"(a):"memory"); return v;}
DEVI unsigned lds32(unsigned a){ unsigned v; asm volatile("ld.shared.u32 %0,[%1];":"=r"(v):"r"(a):"memory"); return v;}
DEVI void sts128(unsigned a, unsigned x,unsigned y,unsigned z,unsigned w){ asm volatile("st.shared.v4.u32 [%0],{%1,%2,%3,%4};"::"r"(a),"r"(x),"r"(y),"r"(z),"r"(w):"memory");}
DEVI void sts64(unsigned a, unsigned x,unsigned y){ asm volatile("st.shared.v2.u32 [%0],{%1,%2};"::"r"(a),"r"(x),"r"(y):"memory");}
DEVI void sts32(unsigned a, unsigned x){ asm volatile("st.shared.u32 [%0],%1;"::"r"(a),"r"(x):"memory");}
DEVI uint4 ldg_relaxed16(const void* p){uint4 v; asm volatile("ld.relaxed.gpu.global.v4.u32 {%0,%1,%2,%3},[%4];":"=r"(v.x),"=r"(v.y),"=r"(v.z),"=r"(v.w):"l"(p):"memory"); return v;}
DEVI unsigned ldg_acquire(const void* p){unsigned v; asm volatile("ld.acquire.gpu.global.u32 %0,[%1];":"=r"(v):"l"(p):"memory"); return v;}
DEVI unsigned ldg_relaxed(const void* p){unsigned v; asm volatile("ld.relaxed.gpu.global.u32 %0,[%1];":"=r"(v):"l"(p):"memory"); return v;}
DEVI void stg_relaxed16(void* p, unsigned a,unsigned b,unsigned c,unsigned d){asm volatile("st.relaxed.gpu.global.v4.u32 [%0],{%1,%2,%3,%4};"::"l"(p),"r"(a),"r"(b),"r"(c),"r"(d):"memory");}
DEVI void stg_relaxed(void* p, unsigned a){asm volatile("st.relaxed.gpu.global.u32 [%0],%1;"::"l"(p),"r"(a):"memory");}
DEVI void stg_release(void* p, unsigned a){asm volatile("st.release.gpu.global.u32 [%0],%1;"::"l"(p),"r"(a):"memory");}
DEVI void red_release_add(void* p, unsigned a){asm volatile("red.release.gpu.global.add.u32 [%0],%1;"::"l"(p),"r"(a):"memory");}
DEVI void fence_gpu(){ asm volatile("fence.acq_rel.gpu;":::"memory"); }
DEVI void red_u64(void* p, unsigned lo, unsigned hi){ asm volatile("{.reg .b64 v; mov.b64 v,{%1,%2}; red.relaxed.gpu.global.add.u64 [%0],v;}"::"l"(p),"r"(lo),"r"(hi):"memory"); }
DEVI float ex2(float x){ float y; asm("ex2.approx.ftz.f32 %0,%1;":"=f"(y):"f"(x)); return y;}
DEVI void cluster_sync(){ asm volatile("barrier.cluster.arrive.release.aligned; barrier.cluster.wait.acquire.aligned;":::"memory"); }
DEVI void spin_delay(int n){
  float x=__int_as_float(0x3f000000+(n&1));
  #pragma unroll 1
  for(int i=0;i<n;i++){
    #pragma unroll
    for(int j=0;j<7;j++) asm volatile("fma.rn.f32 %0,%0,%0,%0;":"+f"(x)); }
  if(x==123.456f) asm volatile("trap;");
}

DEVI void wg_ss_n128_tb(float* d, uint64_t da, uint64_t db, int scale_d){
  asm volatile("{.reg .pred p; setp.ne.b32 p,%66,0;\n"
  "wgmma.mma_async.sync.aligned.m64n128k16.f32.bf16.bf16 {%0,%1,%2,%3,%4,%5,%6,%7,%8,%9,%10,%11,%12,%13,%14,%15,%16,%17,%18,%19,%20,%21,%22,%23,%24,%25,%26,%27,%28,%29,%30,%31,%32,%33,%34,%35,%36,%37,%38,%39,%40,%41,%42,%43,%44,%45,%46,%47,%48,%49,%50,%51,%52,%53,%54,%55,%56,%57,%58,%59,%60,%61,%62,%63},%64,%65,p,1,1,0,1;}"
  :"+f"(d[0]),"+f"(d[1]),"+f"(d[2]),"+f"(d[3]),"+f"(d[4]),"+f"(d[5]),"+f"(d[6]),"+f"(d[7]),"+f"(d[8]),"+f"(d[9]),"+f"(d[10]),"+f"(d[11]),"+f"(d[12]),"+f"(d[13]),"+f"(d[14]),"+f"(d[15]),"+f"(d[16]),"+f"(d[17]),"+f"(d[18]),"+f"(d[19]),"+f"(d[20]),"+f"(d[21]),"+f"(d[22]),"+f"(d[23]),"+f"(d[24]),"+f"(d[25]),"+f"(d[26]),"+f"(d[27]),"+f"(d[28]),"+f"(d[29]),"+f"(d[30]),"+f"(d[31]),"+f"(d[32]),"+f"(d[33]),"+f"(d[34]),"+f"(d[35]),"+f"(d[36]),"+f"(d[37]),"+f"(d[38]),"+f"(d[39]),"+f"(d[40]),"+f"(d[41]),"+f"(d[42]),"+f"(d[43]),"+f"(d[44]),"+f"(d[45]),"+f"(d[46]),"+f"(d[47]),"+f"(d[48]),"+f"(d[49]),"+f"(d[50]),"+f"(d[51]),"+f"(d[52]),"+f"(d[53]),"+f"(d[54]),"+f"(d[55]),"+f"(d[56]),"+f"(d[57]),"+f"(d[58]),"+f"(d[59]),"+f"(d[60]),"+f"(d[61]),"+f"(d[62]),"+f"(d[63]):"l"(da),"l"(db),"r"(scale_d));}

DEVI void wg_rs_n128_tb(float* d, unsigned a0,unsigned a1,unsigned a2,unsigned a3, uint64_t db, int scale_d){
  asm volatile("{.reg .pred p; setp.ne.b32 p,%69,0;\n"
  "wgmma.mma_async.sync.aligned.m64n128k16.f32.bf16.bf16 {%0,%1,%2,%3,%4,%5,%6,%7,%8,%9,%10,%11,%12,%13,%14,%15,%16,%17,%18,%19,%20,%21,%22,%23,%24,%25,%26,%27,%28,%29,%30,%31,%32,%33,%34,%35,%36,%37,%38,%39,%40,%41,%42,%43,%44,%45,%46,%47,%48,%49,%50,%51,%52,%53,%54,%55,%56,%57,%58,%59,%60,%61,%62,%63},{%64,%65,%66,%67},%68,p,1,1,1;}"
  :"+f"(d[0]),"+f"(d[1]),"+f"(d[2]),"+f"(d[3]),"+f"(d[4]),"+f"(d[5]),"+f"(d[6]),"+f"(d[7]),"+f"(d[8]),"+f"(d[9]),"+f"(d[10]),"+f"(d[11]),"+f"(d[12]),"+f"(d[13]),"+f"(d[14]),"+f"(d[15]),"+f"(d[16]),"+f"(d[17]),"+f"(d[18]),"+f"(d[19]),"+f"(d[20]),"+f"(d[21]),"+f"(d[22]),"+f"(d[23]),"+f"(d[24]),"+f"(d[25]),"+f"(d[26]),"+f"(d[27]),"+f"(d[28]),"+f"(d[29]),"+f"(d[30]),"+f"(d[31]),"+f"(d[32]),"+f"(d[33]),"+f"(d[34]),"+f"(d[35]),"+f"(d[36]),"+f"(d[37]),"+f"(d[38]),"+f"(d[39]),"+f"(d[40]),"+f"(d[41]),"+f"(d[42]),"+f"(d[43]),"+f"(d[44]),"+f"(d[45]),"+f"(d[46]),"+f"(d[47]),"+f"(d[48]),"+f"(d[49]),"+f"(d[50]),"+f"(d[51]),"+f"(d[52]),"+f"(d[53]),"+f"(d[54]),"+f"(d[55]),"+f"(d[56]),"+f"(d[57]),"+f"(d[58]),"+f"(d[59]),"+f"(d[60]),"+f"(d[61]),"+f"(d[62]),"+f"(d[63]):"r"(a0),"r"(a1),"r"(a2),"r"(a3),"l"(db),"r"(scale_d));}

DEVI void wg_rs_n64(float* d, unsigned a0,unsigned a1,unsigned a2,unsigned a3, uint64_t db, int scale_d){
  asm volatile("{.reg .pred p; setp.ne.b32 p,%37,0;\n"
  "wgmma.mma_async.sync.aligned.m64n64k16.f32.bf16.bf16 {%0,%1,%2,%3,%4,%5,%6,%7,%8,%9,%10,%11,%12,%13,%14,%15,%16,%17,%18,%19,%20,%21,%22,%23,%24,%25,%26,%27,%28,%29,%30,%31},{%32,%33,%34,%35},%36,p,1,1,0;}"
  :"+f"(d[0]),"+f"(d[1]),"+f"(d[2]),"+f"(d[3]),"+f"(d[4]),"+f"(d[5]),"+f"(d[6]),"+f"(d[7]),"+f"(d[8]),"+f"(d[9]),"+f"(d[10]),"+f"(d[11]),"+f"(d[12]),"+f"(d[13]),"+f"(d[14]),"+f"(d[15]),"+f"(d[16]),"+f"(d[17]),"+f"(d[18]),"+f"(d[19]),"+f"(d[20]),"+f"(d[21]),"+f"(d[22]),"+f"(d[23]),"+f"(d[24]),"+f"(d[25]),"+f"(d[26]),"+f"(d[27]),"+f"(d[28]),"+f"(d[29]),"+f"(d[30]),"+f"(d[31]):"r"(a0),"r"(a1),"r"(a2),"r"(a3),"l"(db),"r"(scale_d));}

DEVI void wg_rs_n16(float* d, unsigned a0,unsigned a1,unsigned a2,unsigned a3, uint64_t db, int scale_d){
  asm volatile("{.reg .pred p; setp.ne.b32 p,%13,0;\n"
  "wgmma.mma_async.sync.aligned.m64n16k16.f32.bf16.bf16 {%0,%1,%2,%3,%4,%5,%6,%7},{%8,%9,%10,%11},%12,p,1,1,0;}"
  :"+f"(d[0]),"+f"(d[1]),"+f"(d[2]),"+f"(d[3]),"+f"(d[4]),"+f"(d[5]),"+f"(d[6]),"+f"(d[7]):"r"(a0),"r"(a1),"r"(a2),"r"(a3),"l"(db),"r"(scale_d));}

DEVI void wg_ss_n8_ta(float* d, uint64_t da, uint64_t db){
  asm volatile("wgmma.mma_async.sync.aligned.m64n8k16.f32.bf16.bf16 {%0,%1,%2,%3},%4,%5,1,1,1,1,0;":"+f"(d[0]),"+f"(d[1]),"+f"(d[2]),"+f"(d[3]):"l"(da),"l"(db));}
DEVI void wg_ss_n8_ta0(float* d, uint64_t da, uint64_t db){
  asm volatile("wgmma.mma_async.sync.aligned.m64n8k16.f32.bf16.bf16 {%0,%1,%2,%3},%4,%5,0,1,1,1,0;":"=f"(d[0]),"=f"(d[1]),"=f"(d[2]),"=f"(d[3]):"l"(da),"l"(db));}
template<int OA,int OB> DEVI void wg_n8_off(float* d, uint64_t da, uint64_t db){
  asm volatile("{.reg .b64 a,b; add.s64 a,%4,%6; add.s64 b,%5,%7; wgmma.mma_async.sync.aligned.m64n8k16.f32.bf16.bf16 {%0,%1,%2,%3},a,b,1,1,1,1,0;}":"+f"(d[0]),"+f"(d[1]),"+f"(d[2]),"+f"(d[3]):"l"(da),"l"(db),"n"(OA),"n"(OB));}
template<int OA,int OB> DEVI void wg_n8_off0(float* d, uint64_t da, uint64_t db){
  asm volatile("{.reg .b64 a,b; add.s64 a,%4,%6; add.s64 b,%5,%7; wgmma.mma_async.sync.aligned.m64n8k16.f32.bf16.bf16 {%0,%1,%2,%3},a,b,0,1,1,1,0;}":"=f"(d[0]),"=f"(d[1]),"=f"(d[2]),"=f"(d[3]):"l"(da),"l"(db),"n"(OA),"n"(OB));}
DEVI void wg_ss_n64_tb(float* d, uint64_t da, uint64_t db){
  asm volatile("wgmma.mma_async.sync.aligned.m64n64k16.f32.bf16.bf16 {%0,%1,%2,%3,%4,%5,%6,%7,%8,%9,%10,%11,%12,%13,%14,%15,%16,%17,%18,%19,%20,%21,%22,%23,%24,%25,%26,%27,%28,%29,%30,%31},%32,%33,1,1,1,0,1;"
  :"+f"(d[0]),"+f"(d[1]),"+f"(d[2]),"+f"(d[3]),"+f"(d[4]),"+f"(d[5]),"+f"(d[6]),"+f"(d[7]),"+f"(d[8]),"+f"(d[9]),"+f"(d[10]),"+f"(d[11]),"+f"(d[12]),"+f"(d[13]),"+f"(d[14]),"+f"(d[15]),"+f"(d[16]),"+f"(d[17]),"+f"(d[18]),"+f"(d[19]),"+f"(d[20]),"+f"(d[21]),"+f"(d[22]),"+f"(d[23]),"+f"(d[24]),"+f"(d[25]),"+f"(d[26]),"+f"(d[27]),"+f"(d[28]),"+f"(d[29]),"+f"(d[30]),"+f"(d[31]):"l"(da),"l"(db));}
DEVI void wg_fence(){ asm volatile("wgmma.fence.sync.aligned;":::"memory"); }
DEVI void wg_commit(){ asm volatile("wgmma.commit_group.sync.aligned;":::"memory"); }
template<int N> DEVI void wg_wait(){ asm volatile("wgmma.wait_group.sync.aligned %0;"::"n"(N):"memory"); }
DEVI uint64_t mkdesc(unsigned addr, unsigned lbo, unsigned sbo){ return (uint64_t)((addr&0x3FFFF)>>4) | ((uint64_t)(lbo>>4)<<16) | ((uint64_t)(sbo>>4)<<32) | (1ull<<62); }
DEVI void tma_load2d(unsigned dst, const void* tm, int c0, int c1, unsigned mb){
  asm volatile("cp.async.bulk.tensor.2d.shared::cluster.global.mbarrier::complete_tx::bytes [%0],[%1,{%3,%4}],[%2];"::"r"(dst),"l"(tm),"r"(mb),"r"(c0),"r"(c1):"memory");}
DEVI void tma_store2d(const void* tm, unsigned src, int c0, int c1){
  asm volatile("cp.async.bulk.tensor.2d.global.shared::cta.bulk_group [%0,{%2,%3}],[%1];"::"l"(tm),"r"(src),"r"(c0),"r"(c1):"memory");}
DEVI void stsm4(unsigned addr, unsigned a, unsigned b, unsigned c, unsigned d){
  asm volatile("stmatrix.sync.aligned.m8n8.x4.shared.b16 [%0],{%1,%2,%3,%4};"::"r"(addr),"r"(a),"r"(b),"r"(c),"r"(d):"memory");}
template<int R> DEVI void reg_alloc(){ asm volatile("setmaxnreg.inc.sync.aligned.u32 %0;"::"n"(R)); }
template<int R> DEVI void reg_dealloc(){ asm volatile("setmaxnreg.dec.sync.aligned.u32 %0;"::"n"(R)); }
#define SKIP 0
#define STAGGER 5
#define POLL2 0
#define PROBE 3
#define LINEB 128
#define PITCH 1024
#define LPJ (256/LINEB)
#define HALFB (32*LPJ*PITCH)
#define SLOTB (2*HALFB)
#define SKEW 1
#define SK(L) (SKEW? ((L)&7)*128 : 0)
#define RELW 4
#define PACE_N 0
#define SPLIT_A 16
__device__ __align__(1024) unsigned char g_kx[64*32*8192];
__device__ __align__(1024) unsigned char g_vx[64*32*8192];
__device__ __align__(1024) unsigned char g_km[64*32*2048];
__device__ __align__(1024) unsigned char g_vm[64*32*2048];
__device__ __align__(131072) unsigned char g_ring[4*SLOTB+8*1024];
__device__ __align__(16) uint4 g_pro[64];
__device__ unsigned g_kvflag[16*32];
__device__ unsigned g_mflag[64*32];
__device__ unsigned g_epoch;
__device__ unsigned g_done;
__device__ unsigned g_dbgclk[64*64*16];
__device__ unsigned long long g_dbgt[64*16];
__device__ unsigned long long g_dbgt2[64*8];
__device__ unsigned g_steps[64*64*2];
__device__ unsigned g_gt[64*64*4];
__device__ unsigned g_gw[64*64*8*2];
__device__ unsigned g_sv[64*64*8];
#define SVT(i) do{ if(DBG==2 && lane==0){ unsigned long long c_; asm volatile("mov.u64 %0,%%clock64;":"=l"(c_)); g_sv[(cta*64+s)*8+(i)]=(unsigned)c_; } }while(0)
#define GTS(i,sidx) do{ if(DBG==3 && lane==0){ unsigned long long a_; asm volatile("mov.u64 %0,%%globaltimer;":"=l"(a_)); g_gt[(cta*64+(sidx))*4+(i)]=(unsigned)a_; } }while(0)
#define TSTAMPV(i) do{ if(DBG && threadIdx.x==256){ unsigned long long a_; asm volatile("mov.u64 %0,%%globaltimer;":"=l"(a_)::"memory"); g_dbgt2[cta*8+(i)]=a_; } }while(0)
#define TSTAMP(i) do{ if(DBG && threadIdx.x==0){ unsigned long long a_,b_; asm volatile("mov.u64 %0,%%globaltimer;":"=l"(a_)); asm volatile("mov.u64 %0,%%clock64;":"=l"(b_)); g_dbgt[cta*16+(i)*2]=a_; g_dbgt[cta*16+(i)*2+1]=b_; } }while(0)

struct ChainArgs { const bf16 *x,*mem0,*Wq,*Wk,*Wv,*Wo; int delay; int adapt; int skip; };
#define MB_WO 56

#define CS_OF    0
#define CS_A     65536
#define CS_X     131072
#define CS_KV    131072
#define CS_MEM   (CS_KV+49152)
#define CS_XQ    (CS_MEM+4096)
#define CS_XV    (CS_XQ+4096)
#define CS_VM    (CS_XV+2112)
#define CS_P     (CS_VM+2048)
#define CS_MISC  196608
#define CS_SPART (CS_MISC+1024)
#define CS_EXP   (CS_SPART+11264)
#define CS_OBUF  (CS_EXP+2048)
#define CS_ZERO  (CS_OBUF+2048)
#define CS_TBL   (CS_ZERO+128)
#define CS_TRACE (CS_TBL+8*1536+4096)
#define CS_TOTAL (CS_TRACE+2560)
#define NSTAGE_KV 3

DEVI int memswz(int r){ return ((r&1)<<2)|(r>>1); }

DEVI void chain_issue_kv(unsigned sb, int seg, int h, unsigned epoch, unsigned pre){
  const unsigned* fl=&g_kvflag[(seg>>2)*32+h]; unsigned tgt=epoch*2; int g=0;
  while((int)(pre-tgt)<0 && ++g<WAIT_LIMIT) pre=ldg_relaxed(fl);
  asm volatile("fence.proxy.async.global;":::"memory");
  int st=seg%NSTAGE_KV; unsigned mb=sb+CS_MISC+st*8; unsigned dst=sb+CS_KV+st*16384;
  mbar_expect(mb,16384);
  bulk_g2s(dst, g_kx+((size_t)seg*32+h)*8192, 8192, mb);
  bulk_g2s(dst+8192, g_vx+((size_t)seg*32+h)*8192, 8192, mb);
}

DEVI void load_tile_qkv(unsigned dst, const bf16* W, int h, int dh, int tid){
  #pragma unroll 1
  for(int i=tid;i<4096;i+=384){ int r=i>>4,c=i&15; int sw=(((r>>3)&3)<<1)|(r&1);
    cpasync16(dst+r*256+((c^sw)<<4), W+(size_t)(dh*256+r)*4096+h*128+c*8); }
}
DEVI void load_tile_wo(unsigned dst, const bf16* W, int h, int dh, int tid){
  #pragma unroll 1
  for(int i=tid;i<4096;i+=384){ int r=i>>5,c=i&31;
    cpasync16(dst+(c>>3)*16384+r*128+(((c&7)^(r&7))<<4), W+((size_t)h*128+r)*512+dh*256+c*8); }
}
DEVI unsigned qkv_ldsm_addr(int et,int j,int u,int lane){
  int mi=lane>>3, kap=lane&7; int r=32*j+8*(kap>>1)+4*u+(kap&1)+2*(mi>>1); int c=2*et+(mi&1);
  int sw=(((r>>3)&3)<<1)|(r&1); return r*256+((c^sw)<<4);
}

#define CKPT(i) do{ if(DBG==2 || (DBG==1 && (i)==2)) { if(dbg){ unsigned long long c_; asm volatile("mov.u64 %0,%%clock64;":"=l"(c_)); if(s<40) sts32(sb+CS_TRACE+(s*16+(i))*4,(unsigned)c_); } } }while(0)

#define CKD(i,dep) do{ if(DBG==2 || (DBG==1 && (i)==2)) { if(dbg){ unsigned long long c_=0; asm volatile("{.reg .pred p; setp.ne.u32 p,%1,0x7fc12345; @p mov.u64 %0,%%clock64;}":"+l"(c_):"r"(dep)); if(s<40) sts32(sb+CS_TRACE+(s*16+(i))*4,(unsigned)c_); } } }while(0)

template<int DBG>
DEVI void chain_qk_role(const ChainArgs& a, const void* tmwo, unsigned sb, int cta, int w, int lane, unsigned epoch){
  const int h=cta>>1, dh=cta&1, tid=w*32+lane; const int g=lane>>2, t=lane&3;
  const bool dbg = DBG && (tid==0);
  unsigned aq[16][4], ak[16][4];
  { float mx=0.f;
    #pragma unroll
    for(int r=0;r<4;r++){ const uint4* p=(const uint4*)(a.x+(size_t)(cta*32+w*4+r)*512); float ss=0.f;
      #pragma unroll
      for(int k=0;k<2;k++){ uint4 v=__ldg(p+lane+32*k); unsigned q[4]={v.x,v.y,v.z,v.w};
        #pragma unroll
        for(int i=0;i<4;i++){ float lo=blo(q[i]),hi=bhi(q[i]); ss+=lo*lo+hi*hi; } }
      #pragma unroll
      for(int o=16;o;o>>=1) ss+=__shfl_xor_sync(~0u,ss,o);
      mx=fmaxf(mx,ss); }
    if(lane==0) sts32(sb+CS_MISC+128+w*4,__float_as_uint(mx)); }
  cpasync_wait<2>(); bar_sync(0,384);
  TSTAMP(1);
  const unsigned qa0=qkv_ldsm_addr(w,0,0,lane);
  #pragma unroll
  for(int j=0;j<8;j++){
    #pragma unroll
    for(int u=0;u<2;u++) ldsm4t(sb+CS_OF+qa0+j*8192+u*1024, aq[j*2+u][0],aq[j*2+u][1],aq[j*2+u][2],aq[j*2+u][3]); }
  bar_sync(0,384);
  if(tid==0){ mbar_expect(sb+CS_MISC+MB_WO,65536);
    for(int b=0;b<4;b++) for(int r=0;r<2;r++) tma_load2d(sb+CS_OF+b*16384+r*8192,tmwo,dh*256+b*64,h*128+r*64,sb+CS_MISC+MB_WO); }
  cpasync_wait<1>(); bar_sync(0,384);
  #pragma unroll
  for(int j=0;j<8;j++){
    #pragma unroll
    for(int u=0;u<2;u++) ldsm4t(sb+CS_A+qa0+j*8192+u*1024, ak[j*2+u][0],ak[j*2+u][1],ak[j*2+u][2],ak[j*2+u][3]); }
  cpasync_wait<0>(); bar_sync(0,384);
  TSTAMP(2);
  bar_sync(0,384);
  TSTAMP(3);
  if(tid==0) asm volatile("mbarrier.arrive.relaxed.cluster.shared::cluster.b64 _, [%0];"::"r"(mapa(sb+CS_MISC+48,dh^1)):"memory");
  mbar_wait(sb+CS_MISC+48,0);
  TSTAMP(4);
  const unsigned rdelta=mapa(sb,dh^1)-sb;
  unsigned tA, bA;
  { const unsigned l16=lane*16; const unsigned boff=CS_MEM+g*512+((t^memswz(g))<<4);
    const int sel=lane>>3, rq=sel&1, rp=(lane>>2)&1, cp=lane&3;
    const int jhA0=8*((w*2)>>2)+((w*2)&3)+4*(sel>>1);
    const unsigned rdoff=dh*HALFB+jhA0*LPJ*PITCH+(LINEB==128? rq*PITCH+SK(2*jhA0+rq)+rp*64+cp*16 : (LINEB==64? (2*rq+rp)*PITCH+cp*16 : ((2*rq+rp)*2+(cp>>1))*PITCH+(cp&1)*16));
    const int r0=4*rq+2*rp;
    const unsigned stA0=CS_MEM+r0*512+cp*4+((jhA0^memswz(r0))<<4);
    unsigned kxa; { int mi=lane>>3; int key=(lane&7)+8*(mi&1); int ch=2*(w&3)+(mi>>1); kxa=CS_KV+(w>>2)*4096+key*128+((ch^(key&7))<<4); }
    unsigned vxa; { int mi=lane>>3; int key=(lane&7)+8*(mi>>1); int ch=2*(w&3)+(mi&1); vxa=CS_KV+8192+(w>>2)*4096+key*128+((ch^(key&7))<<4); }
    const unsigned kmo=CS_EXP+(w>>2)*1024+g*128+t*4+(((2*(w&3))^g)<<4);
    const unsigned spw=CS_SPART+w*1408+t*352+g*4;
    const unsigned pbo=CS_P+g*80+t*4;
    const unsigned ta=sb+CS_TBL+w*1536+l16;
    sts128(ta, kxa,vxa,sb+spw,sb+pbo);
    sts128(ta+512, rdoff,sb+stA0,sb+kmo,sb+CS_SPART+w*176+lane*4);
    sts128(ta+1024, ta, sb+boff, sb+CS_XQ+w*512+l16, 0);
    uint4 q=lds128(ta+1024); tA=q.x; bA=q.y;
  }
  unsigned w0,w1,w2,w3;
  { int r=tid>>5,c=tid&31; uint4 v=__ldg((const uint4*)(a.mem0+r*512+dh*256+c*8)); sts128(sb+CS_MEM+r*512+((c^memswz(r))<<4),v.x,v.y,v.z,v.w); w0=v.x; w1=v.y; w2=v.z; w3=v.w; }
  const float sl2=0.08838834764831845f*1.4426950408889634f;
  int dly=a.delay, okc=0; unsigned stg=0, kph=0;
  #pragma unroll 1
  for(int s=0;s<64;s++){
    bar_sync(1,256);
    if(DBG==1 && tid==0){ unsigned long long a_,b_; asm volatile("mov.u64 %0,%%globaltimer;":"=l"(a_)); asm volatile("mov.u64 %0,%%clock64;":"=l"(b_)); g_steps[(cta*64+s)*2]=(unsigned)a_; g_steps[(cta*64+s)*2+1]=(unsigned)b_; }
    if(w==0 && s>0) GTS(2,s-1);
    if(VSTART==0 && w==0) bar_arrive(5,160);
    uint4 b=lds128(bA);
    uint4 b2=lds128(bA^64);
    { unsigned m=__vimax3_u16x2(w0&0x7fff7fffu,w1&0x7fff7fffu,__vimax3_u16x2(w2&0x7fff7fffu,w3&0x7fff7fffu,0u)); m=max(m&0xffffu,m>>16); m=__reduce_max_sync(~0u,m); if(lane==0) sts32(sb+CS_MISC+96+w*4,m); }
    CKD(2,b.x);
    float cq[4]={0,0,0,0}, ck[4]={0,0,0,0};
    #pragma unroll
    for(int j=0;j<8;j+=2){
      mma16816(cq,aq[2*j][0],aq[2*j][1],aq[2*j][2],aq[2*j][3],b.x,b.y);
      mma16816(ck,ak[2*j][0],ak[2*j][1],ak[2*j][2],ak[2*j][3],b.x,b.y);
      mma16816(cq,aq[2*j+1][0],aq[2*j+1][1],aq[2*j+1][2],aq[2*j+1][3],b.z,b.w);
      mma16816(ck,ak[2*j+1][0],ak[2*j+1][1],ak[2*j+1][2],ak[2*j+1][3],b.z,b.w);
      if(j<6) b=lds128(bA+((j+2)>>1)*128);
      mma16816(cq,aq[2*j+2][0],aq[2*j+2][1],aq[2*j+2][2],aq[2*j+2][3],b2.x,b2.y);
      mma16816(ck,ak[2*j+2][0],ak[2*j+2][1],ak[2*j+2][2],ak[2*j+2][3],b2.x,b2.y);
      mma16816(cq,aq[2*j+3][0],aq[2*j+3][1],aq[2*j+3][2],aq[2*j+3][3],b2.z,b2.w);
      mma16816(ck,ak[2*j+3][0],ak[2*j+3][1],ak[2*j+3][2],ak[2*j+3][3],b2.z,b2.w);
      if(j<6) b2=lds128((bA^64)+((j+2)>>1)*128);
      if(VSTART>0 && j==VSTART-1 && w==0) bar_arrive(5,160);
    }
    const unsigned xqA=tA-CS_TBL-w*1536+CS_XQ+w*512;
    stasync16(xqA+rdelta,pack2(cq[0],cq[1]),pack2(cq[2],cq[3]),pack2(ck[0],ck[1]),pack2(ck[2],ck[3]),sb+rdelta+CS_MISC+24);
    if(tid==0) mbar_expect(sb+CS_MISC+24,4096);
    CKD(3,__float_as_uint(ck[3]));
    unsigned kvpre=0; if(w==6 && lane==0 && s+2<64) kvpre=ldg_relaxed(&g_kvflag[((s+2)>>2)*32+h]);
    if(!(SKIP&4) && w==5 && lane==0 && s>0){ asm volatile("cp.async.bulk.wait_group 0;":::"memory"); asm volatile("red.relaxed.gpu.global.add.u32 [%0],1;"::"l"(&g_mflag[(s-1)*32+h]):"memory"); }
    const uint4 T1=lds128(tA);
    const uint4 T2=lds128(tA+512);
    if(!(SKIP&8)||s<3) mbar_wait(sb+CS_MISC+stg*8,kph);
    unsigned kx0[4],kx1[4]; const unsigned kvs=sb+stg*16384;
    ldsm4(kvs+T1.x,kx0[0],kx0[1],kx0[2],kx0[3]); ldsm4(kvs+T1.x+2048,kx1[0],kx1[1],kx1[2],kx1[3]);
    mbar_wait(sb+CS_MISC+24,s&1);
    { uint4 p=lds128(xqA);
      CKD(4,p.x);
      cq[0]+=blo(p.x); cq[1]+=bhi(p.x); cq[2]+=blo(p.y); cq[3]+=bhi(p.y);
      ck[0]+=blo(p.z); ck[1]+=bhi(p.z); ck[2]+=blo(p.w); ck[3]+=bhi(p.w); }
    unsigned bq0=movm(pack2(cq[0],cq[1])), bq1=movm(pack2(cq[2],cq[3]));
    unsigned ak0=movm(pack2(ck[0],ck[1])), ak2=movm(pack2(ck[2],ck[3]));
    if(s<63){
      float sm[4]={0,0,0,0}, s0[4]={0,0,0,0}, s1[4]={0,0,0,0};
      mma16816(s0,kx0[0],kx0[1],kx0[2],kx0[3],bq0,bq1);
      mma16816(s1,kx1[0],kx1[1],kx1[2],kx1[3],bq0,bq1);
      mma16816(sm,ak0,0u,ak2,0u,bq0,bq1);
      CKD(13,__float_as_uint(sm[0]));
      const unsigned spw=T1.z;
      sts32(spw+32,__float_as_uint(s0[0])); sts32(spw+176+32,__float_as_uint(s0[1]));
      sts32(spw+64,__float_as_uint(s0[2])); sts32(spw+176+64,__float_as_uint(s0[3]));
      sts32(spw+96,__float_as_uint(s1[0])); sts32(spw+176+96,__float_as_uint(s1[1]));
      sts32(spw+128,__float_as_uint(s1[2])); sts32(spw+176+128,__float_as_uint(s1[3]));
      sts32(spw,__float_as_uint(sm[0])); sts32(spw+176,__float_as_uint(sm[1]));
      bar_sync(2,256);
      unsigned vx0[4],vx1[4];
      { const unsigned rb=T2.w, rm=(rb-(lane*4))+((lane&7)*4);
        float xs[8], ms_[8];
        #pragma unroll
        for(int i=0;i<8;i++) xs[i]=__uint_as_float(lds32(rb+32+i*1408));
        #pragma unroll
        for(int i=0;i<8;i++) ms_[i]=__uint_as_float(lds32(rm+i*1408));
        CKD(5,__float_as_uint(xs[0]));
        float x=((xs[0]+xs[1])+(xs[2]+xs[3]))+((xs[4]+xs[5])+(xs[6]+xs[7]));
        float m_=((ms_[0]+ms_[1])+(ms_[2]+ms_[3]))+((ms_[4]+ms_[5])+(ms_[6]+ms_[7]));
        ldsm4t(kvs+T1.y,vx0[0],vx0[1],vx0[2],vx0[3]); ldsm4t(kvs+T1.y+2048,vx1[0],vx1[1],vx1[2],vx1[3]);
        float mx=fmaxf(x,m_);
        int mi=__float_as_int(mx); mi^=(mi>>31)&0x7fffffff; mi=__reduce_max_sync(~0u,mi); mi^=(mi>>31)&0x7fffffff;
        float nb=-__int_as_float(mi)*sl2;
        float px=ex2(fmaf(x,sl2,nb)), pm=ex2(fmaf(m_,sl2,nb));
        unsigned pk=pack2(px,pm);
        const unsigned pw=sb+CS_P+w*80+lane*2;
        asm volatile("st.shared.u16 [%0],%1;"::"r"(pw+16),"h"((unsigned short)(pk&0xffff)):"memory");
        if(lane<8) asm volatile("st.shared.u16 [%0],%1;"::"r"(pw),"h"((unsigned short)(pk>>16)):"memory");
      }
      bar_sync(3,384);
      if(ANN && w==1 && lane==0) asm volatile("red.relaxed.gpu.global.add.u32 [%0],1;"::"l"(g_ring+4*SLOTB+((s&3)*2+dh)*1024):"memory");
      { const unsigned pb=T1.w;
        unsigned p0=lds32(pb+16), p1=lds32(pb+32), p2=lds32(pb+48), p3=lds32(pb+64), pm=lds32(pb);
        uint2 am=lds64(sb+CS_VM+w*256+lane*8);
        CKD(7,p0);
        float oa[4]={0,0,0,0}, ob[4]={0,0,0,0}, la[4]={0,0,0,0}, lb[4]={0,0,0,0}; const unsigned ONE=0x3F803F80u;
        mma16816(la,ONE,ONE,ONE,ONE,p0,p1);
        mma16816(lb,ONE,ONE,ONE,ONE,p2,p3);
        mma16816(oa,vx0[0],vx0[1],vx0[2],vx0[3],p0,p1);
        mma16816(ob,vx1[0],vx1[1],vx1[2],vx1[3],p2,p3);
        mma1688(la,ONE,ONE,pm);
        mma1688(oa,am.x,am.y,pm);
        float i0,i1; asm("rcp.approx.ftz.f32 %0,%1;":"=f"(i0):"f"(la[0]+lb[0])); asm("rcp.approx.ftz.f32 %0,%1;":"=f"(i1):"f"(la[1]+lb[1]));
        unsigned b0=movm(pack2((oa[0]+ob[0])*i0,(oa[1]+ob[1])*i1)), b1=movm(pack2((oa[2]+ob[2])*i0,(oa[3]+ob[3])*i1));
        const unsigned oa_=T2.z-CS_EXP+CS_OBUF;
        sts32(oa_,b0); sts32(oa_^16,b1);
        asm volatile("fence.proxy.async.shared::cta;":::"memory");
        bar_arrive(6,384);
        CKD(8,b0);
      }
    }
    if(dh==0){ sts32(T2.z,ak0); sts32(T2.z^16,ak2); asm volatile("fence.proxy.async.shared::cta;":::"memory"); }
    if(w==5) SVT(0);
    if(w==6) SVT(3);
    if(w==5){ bar_sync(7,384); SVT(1);
      if(!(SKIP&4) && lane==0){
        unsigned char* dst=(dh? g_vm: g_km)+((size_t)s*32+h)*2048;
        bulk_s2g(dst,sb+CS_EXP,2048);
        if(s>=2 && s<62 && !(SKIP&16)){ unsigned char* z=g_ring+((s+2)&3)*SLOTB+dh*HALFB+h*LPJ*PITCH+SK(2*h); for(int l=0;l<LPJ;l++) bulk_s2g(z+l*(PITCH+SK(1)),sb+CS_ZERO,LINEB);
          if(h==0) bulk_s2g(g_ring+4*SLOTB+(((s+2)&3)*2+dh)*1024,sb+CS_ZERO,16); }
        asm volatile("cp.async.bulk.commit_group;":::"memory");
        if(s==63){ asm volatile("cp.async.bulk.wait_group 0;":::"memory"); asm volatile("red.relaxed.gpu.global.add.u32 [%0],1;"::"l"(&g_mflag[63*32+h]):"memory"); }
      }
      __syncwarp(); SVT(2);
    } else bar_arrive(7,384);
    if(!(SKIP&8) && w==6 && lane==0 && s+2<64) chain_issue_kv(sb,s+2,h,epoch,kvpre);
    if(w==6) SVT(4);
    if(w==0) SVT(5);
    if(++stg==NSTAGE_KV){ stg=0; kph^=1; }
    if(s==63){ TSTAMP(5); break; }
    if(s==0) TSTAMP(6);
    { const unsigned char* p=g_ring+(T2.x+(s&3)*SLOTB);
      const unsigned stA0=T2.y;
      bar_sync(4,384);
      if(w==0) SVT(6);
      float ds=__uint_as_float(lds32(sb+CS_MISC+68));
      spin_delay(dly);
      uint4 x0,x1; int gd=0;
      { bool ok;
        do{ x0=ldg_relaxed16(p); x1=ldg_relaxed16(p+LPJ*PITCH+SK(2));
          ok=((x0.x&63)==32)&&((x0.z&63)==32)&&((x1.x&63)==32)&&((x1.z&63)==32); ++gd;
        }while(!__all_sync(~0u,ok) && gd<WAIT_LIMIT && !(SKIP&1)); }
      { const int s_=s; { const int s=s_+1; CKD(1,x0.x); } }
      if(w==0) GTS(1,s); if(w==0 && DBG==3 && lane==0) g_gt[(cta*64+s)*4+3]=gd;
      if(DBG==3 && lane==0){ unsigned long long a_; asm volatile("mov.u64 %0,%%globaltimer;":"=l"(a_)); g_gw[((cta*64+s)*8+w)*2]=(unsigned)a_; g_gw[((cta*64+s)*8+w)*2+1]=gd; }
      #define DEC(lo32,hi32,L,H) { int l_=(int)(__funnelshift_r(lo32,hi32,6)<<3)>>3; int h_=((int)hi32-(l_>>26))>>3; L=(float)l_*ds; H=(float)h_*ds; }
      float l0,h0,l1,h1;
      DEC(x0.x,x0.y,l0,h0); DEC(x0.z,x0.w,l1,h1); w0=pack2(l0,l1); w1=pack2(h0,h1); sts32(stA0,w0); sts32((stA0+512)^64,w1);
      DEC(x1.x,x1.y,l0,h0); DEC(x1.z,x1.w,l1,h1); w2=pack2(l0,l1); w3=pack2(h0,h1); sts32(stA0^16,w2); sts32((stA0+512)^80,w3);
      if(a.adapt){ if(gd>1){ dly+=2; okc=0; } else if(++okc>=a.adapt){ dly=max(dly-1,0); okc=0; } }
      if(DBG==2 && dbg && s+1<40){ sts32(sb+CS_TRACE+((s+1)*16+14)*4,gd); sts32(sb+CS_TRACE+((s+1)*16+15)*4,dly); }
    }
  }
}

template<int DBG,bool FIRST>
DEVI void chain_v_step(unsigned (&W)[32][4], unsigned sb, int cta, int v, int lane, unsigned epoch, int s, unsigned tV, unsigned bA, unsigned rdelta){
  const int h=cta>>1, dh=cta&1; const int tid=256+v*32+lane; const bool dbg = DBG && (tid==256);

    float c0a[4], c0b[4], c1a[4], c1b[4];
    #pragma unroll
    for(int i=0;i<4;i++){ asm volatile("mov.b32 %0,0;":"=f"(c0a[i])); asm volatile("mov.b32 %0,0;":"=f"(c0b[i])); asm volatile("mov.b32 %0,0;":"=f"(c1a[i])); asm volatile("mov.b32 %0,0;":"=f"(c1b[i])); }
    bar_sync(5,160);
    uint4 b=lds128(bA), b2=lds128(bA^64);
    CKD(12,b.x);
    #pragma unroll
    for(int j=0;j<8;j+=2){
      mma16816(c0a,W[j*4][0],W[j*4][1],W[j*4][2],W[j*4][3],b.x,b.y); mma16816(c1a,W[j*4+2][0],W[j*4+2][1],W[j*4+2][2],W[j*4+2][3],b.x,b.y);
      mma16816(c0b,W[j*4+1][0],W[j*4+1][1],W[j*4+1][2],W[j*4+1][3],b.z,b.w); mma16816(c1b,W[j*4+3][0],W[j*4+3][1],W[j*4+3][2],W[j*4+3][3],b.z,b.w);
      if(j<6) b=lds128(bA+((j+2)>>1)*128);
      mma16816(c0a,W[j*4+4][0],W[j*4+4][1],W[j*4+4][2],W[j*4+4][3],b2.x,b2.y); mma16816(c1a,W[j*4+6][0],W[j*4+6][1],W[j*4+6][2],W[j*4+6][3],b2.x,b2.y);
      mma16816(c0b,W[j*4+5][0],W[j*4+5][1],W[j*4+5][2],W[j*4+5][3],b2.z,b2.w); mma16816(c1b,W[j*4+7][0],W[j*4+7][1],W[j*4+7][2],W[j*4+7][3],b2.z,b2.w);
      if(j<6) b2=lds128((bA^64)+((j+2)>>1)*128);
    }
    #pragma unroll
    for(int i=0;i<4;i++){ c0a[i]+=c0b[i]; c1a[i]+=c1b[i]; }
    CKD(0,__float_as_uint(c1a[3]));
    const uint4 T1=lds128(tV+512);
    stasync16(T1.w+rdelta,pack2(c0a[0],c0a[1]),pack2(c0a[2],c0a[3]),pack2(c1a[0],c1a[1]),pack2(c1a[2],c1a[3]),sb+rdelta+CS_MISC+32);
    unsigned mu; { uint4 m0=lds128(sb+CS_MISC+96), m1=lds128(sb+CS_MISC+112); mu=max(max(max(m0.x,m0.y),max(m0.z,m0.w)),max(max(m1.x,m1.y),max(m1.z,m1.w))); }
    if(tid==256){ mbar_expect(sb+CS_MISC+32,2052); stasync4(sb+rdelta+CS_XV+2048,mu,sb+rdelta+CS_MISC+32); }
    const uint4 T=lds128(tV);
    if(FIRST){
      TSTAMPV(4);
      mbar_wait(sb+CS_MISC+MB_WO,0);
      TSTAMPV(5);
      { const int vt=v*32+lane; float n0=0.f,n1=0.f; const unsigned cb=sb+CS_OF+(vt>>5)*16384+(vt&3)*4; const int ch=(vt&31)>>2;
        #pragma unroll 8
        for(int r=0;r<128;r++){ unsigned q=lds32(cb+r*128+((ch^(r&7))<<4)); float lo=blo(q),hi=bhi(q); n0+=lo*lo; n1+=hi*hi; }
        float mx=fmaxf(n0,n1);
        #pragma unroll
        for(int o=16;o;o>>=1) mx=fmaxf(mx,__shfl_xor_sync(~0u,mx,o));
        if(lane==0) sts32(sb+CS_MISC+160+v*4,__float_as_uint(mx)); }
      bar_sync(8,128);
      if(tid==256){ float r2=0.f; for(int i=0;i<8;i++) r2=fmaxf(r2,__uint_as_float(lds32(sb+CS_MISC+128+i*4)));
        float wn=0.f,fv=0.f; for(int i=0;i<4;i++){ wn=fmaxf(wn,__uint_as_float(lds32(sb+CS_MISC+160+i*4))); fv+=__uint_as_float(lds32(sb+CS_MISC+176+i*4)); }
        asm volatile("{.reg .b128 v; .reg .b64 l,h2; mov.b64 l,{%1,%2}; mov.b64 h2,{%3,%4}; mov.b128 v,{l,h2}; st.relaxed.gpu.global.b128 [%0],v;}"::"l"(&g_pro[cta]),"r"(__float_as_uint(wn)),"r"(__float_as_uint(fv)),"r"(__float_as_uint(r2)),"r"(epoch):"memory"); }
    }
    mbar_wait(sb+CS_MISC+32,s&1);
    unsigned am0,am1,an0,an1;
    { uint4 p=lds128(T1.w); unsigned mp=lds32(sb+CS_XV+2048); mu=max(mu,mp);
      am0=pack2(c0a[0]+blo(p.x),c0a[1]+bhi(p.x)); am1=pack2(c0a[2]+blo(p.y),c0a[3]+bhi(p.y));
      an0=pack2(c1a[0]+blo(p.z),c1a[1]+bhi(p.z)); an1=pack2(c1a[2]+blo(p.w),c1a[3]+bhi(p.w)); }
    sts64(T1.z,am0,am1); sts64(T1.z+256,an0,an1);
    if(s<63) bar_arrive(3,384);
    CKD(11,am0);
    if(dh==1){ unsigned y0=movm(am0), y1=movm(am1), y2=movm(an0), y3=movm(an1);
      sts32(T.y,y0); sts32(T.y^16,y1); sts32(T.y^32,y2); sts32(T.y^48,y3);
      asm volatile("fence.proxy.async.shared::cta;":::"memory"); }
    bar_arrive(7,384);
    float cstat=__uint_as_float(T.z), rx=__uint_as_float(T.w);
    if(FIRST){
      TSTAMPV(6);
      if(v==0){
        float wn=0.f,fv=0.f,r2=0.f;
        #pragma unroll
        for(int k=0;k<2;k++){ uint4 q; int gd=0;
          for(;;){ asm volatile("{.reg .b128 v; .reg .b64 l,h2; ld.relaxed.gpu.global.b128 v,[%4]; mov.b128 {l,h2},v; mov.b64 {%0,%1},l; mov.b64 {%2,%3},h2;}":"=r"(q.x),"=r"(q.y),"=r"(q.z),"=r"(q.w):"l"(&g_pro[k*32+lane]):"memory");
            if(__all_sync(~0u,q.w==epoch) || ++gd>=WAIT_LIMIT) break; __nanosleep(100); }
          float f=__uint_as_float(q.y); f+=__shfl_xor_sync(~0u,f,1);
          wn=fmaxf(wn,__uint_as_float(q.x)); fv=fmaxf(fv,f); r2=fmaxf(r2,__uint_as_float(q.z)); }
        #pragma unroll
        for(int o=16;o;o>>=1){ wn=fmaxf(wn,__shfl_xor_sync(~0u,wn,o)); fv=fmaxf(fv,__shfl_xor_sync(~0u,fv,o)); r2=fmaxf(r2,__shfl_xor_sync(~0u,r2,o)); }
        if(lane==0) sts64(sb+CS_MISC+192,__float_as_uint(sqrtf(wn)*sqrtf(fv)*1.06f),__float_as_uint(sqrtf(r2)));
      }
      bar_sync(8,128);
      { const uint2 z=lds64(sb+CS_MISC+192); cstat=__uint_as_float(z.x); rx=__uint_as_float(z.y); }
      sts64(tV+8,__float_as_uint(cstat),__float_as_uint(rx));
      TSTAMPV(7);
    }
    if(s<63){
      float bound=cstat*fmaxf(22.7f*__uint_as_float(mu<<16),rx); bound=fmaxf(bound,1e-30f);
      unsigned eb=(__float_as_uint(bound)>>23)+1; eb=min(max(eb,24u),250u);
      const float enc=__uint_as_float((277u-eb)<<23);
      if(tid==256) sts32(sb+CS_MISC+68,(eb-23u)<<23);
      unsigned char* rp=g_ring+(T.x+(s&3)*SLOTB);
      float cw[4][4];
      const uint64_t da=mkdesc(sb+CS_OF,16,1024), db=mkdesc(sb+CS_OBUF,16,1024);
      bar_sync(6,384);
      #define WK(i,kk) wg_n8_off<(kk)*128,((kk)>>2)*64+((kk)&3)*2>(cw[i],dai,db)
      #define WTILE(i) { const uint64_t dai=da+(uint64_t)((((i)+rot)&3)*1024); wg_n8_off0<0,0>(cw[i],dai,db); WK(i,1); WK(i,2); WK(i,3); WK(i,4); WK(i,5); WK(i,6); WK(i,7); wg_commit(); }
      const int rot=ROT? (h&3): 0;
      wg_fence();
      WTILE(0); WTILE(1);
      const float e0=enc, e1=enc;
      #define WRED(i) { int i0_=__float2int_rn(cw[i][0]*e0), i1_=__float2int_rn(cw[i][1]*e1), i2_=__float2int_rn(cw[i][2]*e0), i3_=__float2int_rn(cw[i][3]*e1); \
          if(i==0) CKD(9,i0_); if(i==3) CKD(10,i3_); \
          if(!(SKIP&16)){ red_u64(rp+(((i)+rot)&3)*8*LPJ*PITCH,   ((unsigned)i0_<<6)|1u, ((unsigned)i1_<<3)+(unsigned)(i0_>>26)); \
          red_u64(rp+(((i)+rot)&3)*8*LPJ*PITCH+LPJ*PITCH+SK(2), ((unsigned)i2_<<6)|1u, ((unsigned)i3_<<3)+(unsigned)(i2_>>26)); } }
      wg_wait<1>(); WRED(0); wg_fence(); WTILE(2); wg_wait<1>(); WRED(1); wg_fence(); WTILE(3); wg_wait<1>(); WRED(2); wg_wait<0>(); WRED(3);
      bar_arrive(4,384);
      if(v==0) GTS(0,s);
    }
}

template<int DBG>
DEVI void chain_v_role(const ChainArgs& a, unsigned sb, int cta, int v, int lane, unsigned epoch){
  const int h=cta>>1, dh=cta&1, tid=256+v*32+lane; const int g=lane>>2, t=lane&3;
  const bool dbg = DBG && (tid==256);
  unsigned W[32][4];
  cpasync_wait<2>(); bar_sync(0,384);
  bar_sync(0,384);
  cpasync_wait<1>(); bar_sync(0,384);
  cpasync_wait<0>(); bar_sync(0,384);
  TSTAMPV(0);
  { const unsigned va=sb+CS_X+qkv_ldsm_addr(2*v,0,0,lane), vb=sb+CS_X+qkv_ldsm_addr(2*v+1,0,0,lane);
    #pragma unroll
    for(int j=0;j<8;j++){
      ldsm4t(va+j*8192,W[j*4][0],W[j*4][1],W[j*4][2],W[j*4][3]); ldsm4t(va+j*8192+1024,W[j*4+1][0],W[j*4+1][1],W[j*4+1][2],W[j*4+1][3]);
      ldsm4t(vb+j*8192,W[j*4+2][0],W[j*4+2][1],W[j*4+2][2],W[j*4+2][3]); ldsm4t(vb+j*8192+1024,W[j*4+3][0],W[j*4+3][1],W[j*4+3][2],W[j*4+3][3]); }
    float fs=0.f;
    float fs2=0.f;
    #pragma unroll 2
    for(int i=v*32+lane;i<4096;i+=256){ uint4 q=lds128(sb+CS_X+i*16), q2=lds128(sb+CS_X+(i+128)*16); const unsigned z[4]={q.x,q.y,q.z,q.w}, z2[4]={q2.x,q2.y,q2.z,q2.w};
      #pragma unroll
      for(int r=0;r<4;r++){ float lo=blo(z[r]),hi=bhi(z[r]); fs=fmaf(lo,lo,fs); fs2=fmaf(hi,hi,fs2); lo=blo(z2[r]); hi=bhi(z2[r]); fs=fmaf(lo,lo,fs); fs2=fmaf(hi,hi,fs2); } }
    fs+=fs2;
    #pragma unroll
    for(int o=16;o;o>>=1) fs+=__shfl_xor_sync(~0u,fs,o);
    if(lane==0) sts32(sb+CS_MISC+176+v*4,__float_as_uint(fs)); }
  TSTAMPV(1);
  bar_sync(0,384);
  TSTAMPV(2);
  mbar_wait(sb+CS_MISC+48,0);
  TSTAMPV(3);
  if(v==1 && lane==0){ for(int s=0;s<2;s++) chain_issue_kv(sb,s,h,epoch,epoch*2-1); }
  const unsigned rdelta=mapa(sb,dh^1)-sb;
  unsigned bA, tV;
  { const unsigned l16=lane*16; const unsigned boff=CS_MEM+g*512+((t^memswz(g))<<4);
    const unsigned redoff=dh*HALFB+v*2*LPJ*PITCH+(LINEB==128? (t>>1)*PITCH+SK(4*v+(t>>1))+(t&1)*64+g*8 : (LINEB==64? t*PITCH+g*8 : (t*2+(g>>2))*PITCH+(g&3)*8));
    const unsigned vmo=CS_EXP+(v>>1)*1024+g*128+t*4; const int c0=2*((2*v)&3);
    const unsigned ta=sb+CS_TBL+8*1536+v*1024+l16;
    sts128(ta, redoff, sb+vmo+(((c0+0)^g)<<4), 0, 0);
    sts128(ta+512, ta, sb+boff, sb+CS_VM+(2*v)*256+lane*8, sb+CS_XV+v*512+l16);
    uint4 q=lds128(ta+512); tV=q.x; bA=q.y; }
  chain_v_step<DBG,true>(W,sb,cta,v,lane,epoch,0,tV,bA,rdelta);
  #pragma unroll 1
  for(int s=1;s<64;s++) chain_v_step<DBG,false>(W,sb,cta,v,lane,epoch,s,tV,bA,rdelta);
}

template<int DBG>
DEVI void chain_role(const ChainArgs& a, const void* tmwo, unsigned sb, int cta, unsigned epoch){
  const int tid=threadIdx.x, lane=tid&31; const int w=__shfl_sync(~0u,tid>>5,0); const int h=cta>>1, dh=cta&1;
  TSTAMP(0);
  if(tid==0){ for(int i=0;i<5;i++) mbar_init(sb+CS_MISC+i*8,1); mbar_init(sb+CS_MISC+48,1); mbar_init(sb+CS_MISC+MB_WO,1); asm volatile("fence.mbarrier_init.release.cluster;":::"memory"); }
  asm volatile("barrier.cluster.arrive.release.aligned; barrier.cluster.wait.aligned;":::"memory");
  if(tid<32){ sts32(sb+CS_ZERO+tid*4,0); asm volatile("fence.proxy.async.shared::cta;":::"memory"); }
  load_tile_qkv(sb+CS_OF,a.Wq,h,dh,tid); cpasync_commit();
  load_tile_qkv(sb+CS_A,a.Wk,h,dh,tid); cpasync_commit();
  load_tile_qkv(sb+CS_X,a.Wv,h,dh,tid); cpasync_commit();
  if(tid>=320){ const int z=tid-320; int slot=z>>4, c=z&15; stg_relaxed16(g_ring+slot*SLOTB+dh*HALFB+h*LPJ*PITCH+((c*16)/LINEB)*PITCH+SK(2*h+(c>>3))+(c*16)%LINEB,0,0,0,0);
    if(h==0 && (z&15)==0) stg_relaxed(g_ring+4*SLOTB+(slot*2+dh)*1024,0u);
    fence_gpu(); }
  if(w<8) chain_qk_role<DBG>(a,tmwo,sb,cta,w,lane,epoch); else chain_v_role<DBG>(a,sb,cta,w-8,lane,epoch);
  if(DBG){ __syncthreads(); for(int i=tid;i<640;i+=384) g_dbgclk[cta*1024+i]=lds32(sb+CS_TRACE+i*4); }
}
__device__ unsigned long long g_cvt[8];
#define CVT(i) do{ if(ca.dbgT && task==0 && tid==0){ unsigned long long g_; asm volatile("mov.u64 %0,%%globaltimer;":"=l"(g_)); g_cvt[i]=g_; } }while(0)
struct ConvArgs { const bf16 *u,*Are,*Aim,*Bre,*Bim,*Cre,*Cim,*logdt,*Dskip; bf16* out; float* dbgK; int dbgT; };
#define NCONV_TASKS 64
#define CV_KP   0
#define CV_KPW  8448
#define CV_U    (8*CV_KPW)
#define CV_UW   5616
#define CV_KT   (CV_U+8*CV_UW)
#define CV_KTW  2576
#define CV_Y    (CV_KT+8*CV_KTW)
#define CV_PR   (CV_Y+32768)
#define CV_IX   (CV_PR+16384)
#define CV_END  (CV_IX+4352)
DEVI void cexp(float re, float im, float& zr, float& zi){
  float m=ex2(re*1.4426950408889634f);
  float r=im*0.15915494309189535f; r-=rintf(r); r*=6.283185307179586f;
  zr=m*__cosf(r); zi=m*__sinf(r);
}
DEVI void csq(float& zr, float& zi){ float a=zr*zr-zi*zi, b=2.f*zr*zi; zr=a; zi=b; }
template<int NT, bool FIRST>
DEVI void conv_phase(float (&acc)[4][4][4], unsigned (&r)[15], unsigned (&nx)[8], unsigned kb, unsigned ub, int d0){
  #pragma unroll 1
  for(int delta=d0;delta<d0+8;delta++){
    #pragma unroll
    for(int i=0;i<7;i++) r[i]=r[i+8];
    #pragma unroll
    for(int i=0;i<8;i++) r[7+i]=nx[i];
    unsigned b[2][8];
    { const unsigned a=ub+(8*(4-NT)-delta)*144; ldsm4(a,b[0][0],b[0][1],b[0][2],b[0][3]); ldsm4(a+64,b[0][4],b[0][5],b[0][6],b[0][7]); }
    if(delta<31){
      #pragma unroll
      for(int i=0;i<8;i++) nx[i]=lds32(kb+(8*delta+8+i)*32); }
    #pragma unroll
    for(int jj=0;jj<NT;jj++){ const int jn=4-NT+jj; const int cur=jj&1;
      if(jj+1<NT){ const unsigned a=ub+(8*(jn+1)-delta)*144; ldsm4(a,b[cur^1][0],b[cur^1][1],b[cur^1][2],b[cur^1][3]); ldsm4(a+64,b[cur^1][4],b[cur^1][5],b[cur^1][6],b[cur^1][7]); }
      #pragma unroll
      for(int kk=0;kk<4;kk++)
      #pragma unroll
      for(int i=0;i<4;i++){ if(FIRST && i<kk && delta==0) continue;
        const int u=7+2*(i-kk);
        mma16816(acc[i][jn],r[u],r[u+1],r[u-1],r[u],b[cur][2*kk],b[cur][2*kk+1]); }
    }
  }
}
DEVI void conv_task(const ConvArgs& ca, unsigned sb, int task, int w, int lane){
  const int d0=task*8, d=d0+w, tid=w*32+lane, g=lane>>2, t=lane&3;
  CVT(0);
  uint4 uv[8];
  #pragma unroll
  for(int i=0;i<8;i++) uv[i]=__ldg((const uint4*)(ca.u+(size_t)(tid+256*i)*512+d0));
  { const int n=d*128+lane*4;
    uint2 are=__ldg((const uint2*)(ca.Are+n)), aim=__ldg((const uint2*)(ca.Aim+n)), bre=__ldg((const uint2*)(ca.Bre+n)), bim=__ldg((const uint2*)(ca.Bim+n)), cre=__ldg((const uint2*)(ca.Cre+n)), cim=__ldg((const uint2*)(ca.Cim+n));
    const float dt=__bfloat162float(__float2bfloat16(expf(__bfloat162float(ca.logdt[d]))));
    #pragma unroll
    for(int e=0;e<4;e++){
      #define EL(v) ((e&1)? bhi(e<2? v.x: v.y): blo(e<2? v.x: v.y))
      const float br=dt*EL(bre), bi=dt*EL(bim), cr=EL(cre), ci=EL(cim);
      sts128(sb+CV_PR+w*2048+(lane*4+e)*16,__float_as_uint(dt*EL(are)),__float_as_uint(dt*EL(aim)),__float_as_uint(cr*br-ci*bi),__float_as_uint(cr*bi+ci*br)); } }
  for(int e=tid;e<2114;e+=256){ const int x=e-65; int idx=641;
    if(x>=0){ const int lr=(int)__bfloat162float(__float2bfloat16((float)x)); if(lr<256) idx=lr; else { const int k=(31-__clz(lr))-7; idx= lr==2048? 640 : 256+(k-1)*128+((lr>>k)-128); } }
    asm volatile("st.shared.u16 [%0],%1;"::"r"(sb+CV_IX+e*2),"h"((unsigned short)idx):"memory"); }
  for(int i=tid;i<8*7*9;i+=256){ int c=i/63, rem=i%63; sts128(sb+CV_U+c*CV_UW+(rem/9)*144+(rem%9)*16,0,0,0,0); }
  #pragma unroll
  for(int i=0;i<8;i++){ const int tt=tid+256*i; const unsigned q[4]={uv[i].x,uv[i].y,uv[i].z,uv[i].w};
    const unsigned o=sb+CV_U+((tt>>6)+7)*144+(tt&63)*2;
    #pragma unroll
    for(int c=0;c<4;c++){ asm volatile("st.shared.u16 [%0],%1;"::"r"(o+(2*c)*CV_UW),"h"((unsigned short)(q[c]&0xffff)):"memory"); asm volatile("st.shared.u16 [%0],%1;"::"r"(o+(2*c+1)*CV_UW),"h"((unsigned short)(q[c]>>16)):"memory"); } }
  bar_sync(11,256);
  CVT(1);
  float c0[4]={0,0,0,0},c0b[4]={0,0,0,0},c1[4]={0,0,0,0},c2[4]={0,0,0,0},c3[4]={0,0,0,0}; float klast=0.f;
  #pragma unroll 2
  for(int ks=0;ks<16;ks++){
    float yr[2][2],yi[2][2],er[2][2],ei[2][2],cbr[2],cbi[2];
    #pragma unroll
    for(int q=0;q<2;q++){ const uint4 pr=lds128(sb+CV_PR+w*2048+(8*ks+4*q+t)*16);
      const float ar=__uint_as_float(pr.x), ai=__uint_as_float(pr.y); cbr[q]=__uint_as_float(pr.z); cbi[q]=__uint_as_float(pr.w);
      cexp(ar*(float)g,ai*(float)g,yr[q][0],yi[q][0]); cexp(ar*(float)(g+8),ai*(float)(g+8),yr[q][1],yi[q][1]);
      cexp(ar*(float)(16*g),ai*(float)(16*g),er[q][0],ei[q][0]); cexp(ar*(float)(16*g+128),ai*(float)(16*g+128),er[q][1],ei[q][1]); }
    #define AFR() pack2(yr[0][0],yi[0][0]),pack2(yr[0][1],yi[0][1]),pack2(yr[1][0],yi[1][0]),pack2(yr[1][1],yi[1][1])
    #define BFR(q,h) pack2(cbr[q]*er[q][h]-cbi[q]*ei[q][h], -(cbr[q]*ei[q][h]+cbi[q]*er[q][h]))
    mma16816(c0,AFR(),BFR(0,0),BFR(1,0));
    mma16816(c0b,AFR(),BFR(0,1),BFR(1,1));
    #define SQ() { csq(yr[0][0],yi[0][0]); csq(yr[0][1],yi[0][1]); csq(yr[1][0],yi[1][0]); csq(yr[1][1],yi[1][1]); csq(er[0][1],ei[0][1]); csq(er[1][1],ei[1][1]); }
    SQ(); mma16816(c1,AFR(),BFR(0,1),BFR(1,1));
    SQ(); mma16816(c2,AFR(),BFR(0,1),BFR(1,1));
    SQ(); mma16816(c3,AFR(),BFR(0,1),BFR(1,1));
  }
  #pragma unroll
  for(int e=0;e<4;e++){ const uint4 pr=lds128(sb+CV_PR+w*2048+(e*32+lane)*16); float zr,zi; cexp(__uint_as_float(pr.x)*2048.f,__uint_as_float(pr.y)*2048.f,zr,zi); klast+=__uint_as_float(pr.z)*zr-__uint_as_float(pr.w)*zi; }
  CVT(2);
  #pragma unroll
  for(int o=16;o;o>>=1) klast+=__shfl_xor_sync(~0u,klast,o);
  { const unsigned kt=sb+CV_KT+w*CV_KTW;
    #define PUT(base,c) { sts32(kt+((base)+16*(2*t)+g)*4,__float_as_uint(c[0])); sts32(kt+((base)+16*(2*t+1)+g)*4,__float_as_uint(c[1])); sts32(kt+((base)+16*(2*t)+g+8)*4,__float_as_uint(c[2])); sts32(kt+((base)+16*(2*t+1)+g+8)*4,__float_as_uint(c[3])); }
    PUT(0,c0); PUT(128,c0b); PUT(256,c1); PUT(384,c2); PUT(512,c3);
    if(lane==0){ sts32(kt+640*4,__float_as_uint(klast)); sts32(kt+641*4,0u); }
    __syncwarp();
    const unsigned kp=sb+CV_KP+w*CV_KPW;
    #pragma unroll 6
    for(int x0=0;x0<2112;x0+=32){ const int e=x0+lane;
      unsigned short i1,i0; asm volatile("ld.shared.u16 %0,[%1];":"=h"(i1):"r"(sb+CV_IX+(e+1)*2)); asm volatile("ld.shared.u16 %0,[%1];":"=h"(i0):"r"(sb+CV_IX+e*2));
      const float kv=__uint_as_float(lds32(kt+i1*4)), km1=__uint_as_float(lds32(kt+i0*4));
      if(ca.dbgK && e>=64) ca.dbgK[d*2048+e-64]=kv;
      sts32(kp+e*4,pack2(kv,km1)); }
    __syncwarp();
  }
  CVT(3);
  float acc[4][4][4];
  #pragma unroll
  for(int i=0;i<4;i++)
  #pragma unroll
  for(int j=0;j<4;j++){ acc[i][j][0]=acc[i][j][1]=acc[i][j][2]=acc[i][j][3]=0.f; }
  const unsigned kb=sb+CV_KP+w*CV_KPW+(64+g-2*t)*4;
  const unsigned ub=sb+CV_U+w*CV_UW+((lane&7)+7)*144+(lane>>3)*16;
  unsigned r[15], nx[8];
  #pragma unroll
  for(int i=8;i<15;i++) r[i]=lds32(kb+(i-15)*32);
  #pragma unroll
  for(int i=0;i<8;i++) nx[i]=lds32(kb+i*32);
  conv_phase<4,true>(acc,r,nx,kb,ub,0);
  conv_phase<3,false>(acc,r,nx,kb,ub,8);
  conv_phase<2,false>(acc,r,nx,kb,ub,16);
  conv_phase<1,false>(acc,r,nx,kb,ub,24);
  CVT(4);
  #pragma unroll
  for(int i=0;i<4;i++)
  #pragma unroll
  for(int j=0;j<4;j++)
  #pragma unroll
  for(int e=0;e<4;e++){ const int b=16*i+g+8*(e>>1), a=8*j+2*t+(e&1); bf16 v=__float2bfloat16(acc[i][j][e]);
    asm volatile("st.shared.u16 [%0],%1;"::"r"(sb+CV_Y+(a*64+b)*16+w*2),"h"(*(unsigned short*)&v):"memory"); }
  bar_sync(11,256);
  CVT(5);
  { uint4 dv=__ldg((const uint4*)(ca.Dskip+d0)); const unsigned dq[4]={dv.x,dv.y,dv.z,dv.w};
    #pragma unroll
    for(int i=0;i<8;i++){ const int tt=tid+256*i; uint4 yv=lds128(sb+CV_Y+tt*16);
      const unsigned uq[4]={uv[i].x,uv[i].y,uv[i].z,uv[i].w}, yq[4]={yv.x,yv.y,yv.z,yv.w}; unsigned o[4];
      #pragma unroll
      for(int c=0;c<4;c++){ unsigned s=pack2(blo(uq[c])*blo(dq[c]),bhi(uq[c])*bhi(dq[c])); o[c]=pack2(blo(yq[c])+blo(s),bhi(yq[c])+bhi(s)); }
      *(uint4*)(ca.out+(size_t)tt*1024+d0)=make_uint4(o[0],o[1],o[2],o[3]); } }
  CVT(6);
}
__device__ __align__(1024) bf16 g_o[2048*4096];
__device__ __align__(1024) float g_part[4*4*8*128*128];
__device__ unsigned g_oflag[16*32];
__device__ unsigned g_pcnt[16*4+8];
struct WorkMaps { CUtensorMap x, wq, wk, wv, wo, o, o64, out64; };
struct WorkArgs { bf16* out; int nw; };
#define WS_STAGE 0
#define WS_KX    131072
#define WS_VX    163840
#define WS_KM    196608
#define WS_VM    204800
#define WS_BAR   212992
#define WS_END   (WS_BAR+256)
enum { TK_KV=0, TK_CONV=1, TK_ATT=2, TK_WO=3, TK_END=4, TK_WOT=5 };
struct Task { int type, m, n, ks, nsplit; };
DEVI int t3_nsplit(int m){ return m<12?1:(m==12?2:(m==13?4:8)); }
struct TaskIter {
  int wk,nw,phase,i;
  DEVI void init(int wk_,int nw_){ wk=wk_; nw=nw_; phase=0; i=wk_; }
  DEVI Task next(){
    Task t; t.ks=0; t.nsplit=1; t.m=0; t.n=0;
    if(phase==0){ if(i<1024){ t.type=TK_KV; t.m=i>>6; t.n=i&63; i+=nw; return t; } phase=1; i=wk; }
    if(phase==1){ if(i<NCONV_TASKS){ t.type=TK_CONV; t.n=i; i+=nw; return t; } phase=2; i=wk; }
    if(nw>=96 || nw<48){
      int j=i;
      for(int m=0;m<=16;m++){
        if(m<16){ if(j<32){ t.type=TK_ATT; t.m=m; t.n=j; i+=nw; return t; } j-=32; }
        if(m>=1 && m<16){ int ns=t3_nsplit(m-1); int c=4*ns; if(j<c){ t.type=TK_WO; t.m=m-1; t.n=j/ns; t.ks=j%ns; t.nsplit=ns; i+=nw; return t; } j-=c; }
        if(m==16){ if(j<64 && nw>=8){ t.type=TK_WOT; t.m=15; t.n=j>>3; t.ks=j&7; t.nsplit=8; i+=nw; return t; } }
      }
      t.type=TK_END; return t;
    }
    if(phase==2){
      if(wk<32){ if(i<wk+16){ t.type=TK_ATT; t.m=i-wk; t.n=wk; i++; return t; } }
      else { const int nb=nw-32; int j=(i==wk)? wk-32 : i-1000;
        int jj=j;
        for(int m=0;m<15;m++){ int ns=t3_nsplit(m); int c=4*ns; if(jj<c){ t.type=TK_WO; t.m=m; t.n=jj/ns; t.ks=jj%ns; t.nsplit=ns; i=1000+j+nb; return t; } jj-=c; } }
      phase=3; i= wk>=32? wk-32 : (nw-32)+wk;
    }
    if(i<64){ t.type=TK_WOT; t.m=15; t.n=i>>3; t.ks=i&7; t.nsplit=8; i+=nw; return t; }
    t.type=TK_END; return t;
  }
};
DEVI void wait_flag(const unsigned* p, unsigned tgt){ int g=0; while((int)(ldg_acquire(p)-tgt)<0 && ++g<WAIT_LIMIT){ __nanosleep(64);} }

DEVI void poll_all(const unsigned* p, unsigned tgt, bool need){
  int g=0; for(;;){ bool ok= !need || (int)(ldg_relaxed(p)-tgt)>=0; if(__all_sync(~0u,ok) || ++g>WAIT_LIMIT) break; __nanosleep(20); }
  asm volatile("fence.proxy.async.global;":::"memory");
}
DEVI void worker_producer(const WorkMaps& mp, unsigned sb, int wk, int nw, unsigned epoch, int lane){
  TaskIter it; it.init(wk,nw); unsigned st=0, ph=1, ntask=0; bool prevconv=false;
  const unsigned B=sb+WS_BAR;
  for(;;){ Task t=it.next(); if(t.type==TK_END) break;
    if(t.type==TK_CONV){ if(ntask>0) mbar_wait(B+80,(ntask-1)&1); prevconv=true; ntask++; continue; }
    if(prevconv){ mbar_wait(B+80,(ntask-1)&1); prevconv=false; }
    const bool wo= t.type==TK_WO || t.type==TK_WOT;
    const int nkb = wo ? 64/t.nsplit : 8; const int kb0 = wo ? t.ks*nkb : 0;
    unsigned ready=0;
    for(int kb=kb0;kb<kb0+nkb;kb++){
      if(wo && (kb&1)==0 && !((ready>>(kb>>1))&1)){
        int g=0; for(;;){ bool ok=(int)(ldg_relaxed(&g_oflag[t.m*32+lane])-epoch)>=0; ready=__ballot_sync(~0u,ok); if(((ready>>(kb>>1))&1) || ++g>WAIT_LIMIT) break; if(t.m<14) __nanosleep(40); }
        asm volatile("fence.proxy.async.global;":::"memory");
      }
      mbar_wait(B+32+st*8,ph);
      if(lane==0){
        const unsigned full=B+st*8, sa=sb+WS_STAGE+st*32768;
        mbar_expect(full,t.type==TK_WOT? 24576: 32768);
        if(t.type==TK_WOT){ tma_load2d(sa,&mp.o64,kb*64,t.m*128+(t.n>>2)*64,full); tma_load2d(sa+16384,&mp.wo,(t.n&3)*128,kb*64,full); tma_load2d(sa+24576,&mp.wo,(t.n&3)*128+64,kb*64,full); }
        else if(t.type==TK_WO){ tma_load2d(sa,&mp.o,kb*64,t.m*128,full); tma_load2d(sa+16384,&mp.wo,t.n*128,kb*64,full); tma_load2d(sa+24576,&mp.wo,t.n*128+64,kb*64,full); }
        else { const CUtensorMap* w= t.type==TK_ATT? &mp.wq : (t.n<32? &mp.wk : &mp.wv); const int col=(t.n&31)*128;
          tma_load2d(sa,&mp.x,kb*64,t.m*128,full); tma_load2d(sa+16384,w,col,kb*64,full); tma_load2d(sa+24576,w,col+64,kb*64,full); }
      }
      __syncwarp();
      if(++st==4){ st=0; ph^=1; }
    }
    ntask++;
  }
}
DEVI void worker_aux(unsigned sb, int wk, int nw, unsigned epoch, int lane){
  TaskIter it; it.init(wk,nw); unsigned ntask=0; const unsigned B=sb+WS_BAR;
  for(;;){ Task t=it.next(); if(t.type==TK_END) break;
    if(ntask>0) mbar_wait(B+80,(ntask-1)&1);
    if(t.type==TK_ATT){
      const int sg=lane&3, eh=(lane>>2)&1;
      poll_all(&g_kvflag[t.m*32+t.n],epoch*2,lane==0);
      { size_t off=((size_t)(t.m*4+sg)*32+t.n)*8192+eh*4096;
        if(lane==0) mbar_expect(B+64,65536);
        __syncwarp();
        if(lane<8) bulk_g2s(sb+WS_KX+eh*16384+sg*4096,g_kx+off,4096,B+64); else if(lane<16) bulk_g2s(sb+WS_VX+eh*16384+sg*4096,g_vx+off,4096,B+64); }
      poll_all(&g_mflag[(t.m*4+sg)*32+t.n],epoch*2,lane<4);
      { size_t off=((size_t)(t.m*4+sg)*32+t.n)*2048+eh*1024;
        if(lane==0) mbar_expect(B+72,16384);
        __syncwarp();
        if(lane<8) bulk_g2s(sb+WS_KM+eh*4096+sg*1024,g_km+off,1024,B+72); else if(lane<16) bulk_g2s(sb+WS_VM+eh*4096+sg*1024,g_vm+off,1024,B+72); }
      __syncwarp();
    }
    ntask++;
  }
}
DEVI void worker_storer(const WorkMaps& mp, unsigned sb, int wk, int nw, unsigned epoch, int lane){
  TaskIter it; it.init(wk,nw); const unsigned B=sb+WS_BAR;
  for(;;){ Task t=it.next(); if(t.type==TK_END) break;
    bar_sync(10,288);
    if(lane==0){
      if(t.type==TK_KV){ unsigned char* g=(t.n<32? g_kx: g_vx);
        for(int sg=0;sg<4;sg++) bulk_s2g(g+((size_t)(t.m*4+sg)*32+(t.n&31))*8192, sb+WS_KX+sg*8192, 8192);
      } else if(t.type==TK_ATT){
        for(int r=0;r<2;r++) for(int eh=0;eh<2;eh++) tma_store2d(&mp.o64,sb+WS_KX+eh*16384+r*8192,t.n*128+eh*64,t.m*128+r*64);
      } else if(t.type==TK_WO && t.nsplit==1){
        for(int r=0;r<2;r++) for(int eh=0;eh<2;eh++) tma_store2d(&mp.out64,sb+WS_KX+eh*16384+r*8192,512+t.n*128+eh*64,t.m*128+r*64);
      }
      asm volatile("cp.async.bulk.commit_group;":::"memory");
      asm volatile("cp.async.bulk.wait_group.read 0;":::"memory");
      mbar_arrive(B+80);
      asm volatile("cp.async.bulk.wait_group 0;":::"memory");
      if(t.type==TK_KV) asm volatile("red.relaxed.gpu.global.add.u32 [%0],1;"::"l"(&g_kvflag[t.m*32+(t.n&31)]):"memory");
      else if(t.type==TK_ATT) stg_relaxed(&g_oflag[t.m*32+t.n],epoch);
    }
    __syncwarp();
  }
}
DEVI void stage_tile(const float* acc, unsigned base, unsigned ehstride, int wi, int lane){
  const int row=16*wi+(lane&7)+8*((lane>>3)&1);
  #pragma unroll
  for(int jp=0;jp<8;jp++){ const int j=2*jp; const int eh=j>>3, c=(j&7)+(lane>>4);
    stsm4(base+eh*ehstride+row*128+((c^(row&7))<<4), pack2(acc[4*j],acc[4*j+1]), pack2(acc[4*j+2],acc[4*j+3]), pack2(acc[4*j+4],acc[4*j+5]), pack2(acc[4*j+6],acc[4*j+7])); }
}
__device__ unsigned long long g_wtrace[68*64*2];
__device__ unsigned long long g_wph[64];
#define WPH(c,i) do{ if(DBG && (c) && w==0 && lane==0){ unsigned long long g_; asm volatile("mov.u64 %0,%%globaltimer;":"=l"(g_)); g_wph[i]=g_; } }while(0)
template<int DBG>
DEVI void worker_consumer(const WorkArgs& wa, const ConvArgs& ca, unsigned sb, int wk, int nw, unsigned epoch, int w, int lane){
  TaskIter it; it.init(wk,nw); unsigned st=0, ph=0, natt=0, ntask=0; const unsigned B=sb+WS_BAR;
  const int r=w>>2, wi=w&3, g=lane>>2, tq=lane&3;
  for(;;){ Task t=it.next();
    if(DBG && w==0 && lane==0 && ntask<64){ unsigned long long g_; asm volatile("mov.u64 %0,%%globaltimer;":"=l"(g_)); g_wtrace[(wk*64+ntask)*2]=g_; g_wtrace[(wk*64+ntask)*2+1]=t.type*1000000+t.m*1000+t.n; }
    if(t.type==TK_END) break;
    if(t.type==TK_CONV){ if(ntask>0) mbar_wait(B+80,(ntask-1)&1); conv_task(ca,sb,t.n,w,lane); asm volatile("fence.proxy.async.shared::cta;":::"memory"); bar_sync(10,288); ntask++; continue; }
    if(t.type==TK_WOT){
      const bool trT= t.n==4 && t.ks==4; WPH(trT,40);
      float ac[32];
      #pragma unroll
      for(int i=0;i<32;i++) ac[i]=0.f;
      for(int kb=0;kb<8;kb++){
        mbar_wait(B+st*8,ph);
        const unsigned sa=sb+WS_STAGE+st*32768;
        const uint64_t da=mkdesc(sa,16,1024), db=mkdesc(sa+16384+r*8192,8192,1024);
        wg_fence();
        #pragma unroll
        for(int k=0;k<4;k++) wg_ss_n64_tb(ac,da+k*2,db+k*128);
        wg_commit();
        if(kb>0){ wg_wait<1>(); if(lane==0) mbar_arrive(B+32+((st+3)&3)*8); }
        if(++st==4){ st=0; ph^=1; }
      }
      wg_wait<0>(); if(lane==0) mbar_arrive(B+32+((st+3)&3)*8);
      WPH(trT,41);
      float* pb=g_part+(size_t)3*524288+(size_t)t.n*8*8192;
      float* p=pb+(size_t)t.ks*8192+(16*wi+g)*128+r*64+2*tq;
      #pragma unroll
      for(int j=0;j<8;j++){ *(float2*)(p+8*j)=make_float2(ac[4*j],ac[4*j+1]); *(float2*)(p+8*128+8*j)=make_float2(ac[4*j+2],ac[4*j+3]); }
      WPH(trT,42);
      __threadfence(); bar_sync(11,256);
      WPH(trT,43);
      if(w==0&&lane==0){ asm volatile("red.relaxed.gpu.global.add.u32 [%0],1;"::"l"(&g_pcnt[64+t.n]):"memory"); int gg=0; while((int)(ldg_relaxed(&g_pcnt[64+t.n])-epoch*8)<0 && ++gg<WAIT_LIMIT); }
      bar_sync(11,256);
      WPH(trT,44);
      { const int tid=w*32+lane; const int rr=t.ks*8+(tid>>5), c4=(tid&31)*4; float4 v[8];
        #pragma unroll
        for(int k=0;k<8;k++) v[k]=__ldcg((const float4*)(pb+(size_t)k*8192+rr*128+c4));
        float4 s4=v[0];
        #pragma unroll
        for(int k=1;k<8;k++){ s4.x+=v[k].x; s4.y+=v[k].y; s4.z+=v[k].z; s4.w+=v[k].w; }
        uint2 o; o.x=pack2(s4.x,s4.y); o.y=pack2(s4.z,s4.w);
        *(uint2*)(wa.out+(size_t)(t.m*128+(t.n>>2)*64+rr)*1024+512+(t.n&3)*128+c4)=o; }
      WPH(trT,45);
      bar_sync(10,288);
      ntask++; continue;
    }
    const bool trA= t.type==TK_ATT && t.m==7 && t.n==24, trW= t.type==TK_WO && t.m==15 && t.n==2 && t.ks==0, trK= t.type==TK_KV && t.m==5 && t.n==20;
    WPH(trA,0); WPH(trW,16); WPH(trK,32);
    float acc[64];
    #pragma unroll
    for(int i=0;i<64;i++) acc[i]=0.f;
    const int nkb = t.type==TK_WO ? 64/t.nsplit : 8;
    for(int kb=0;kb<nkb;kb++){
      mbar_wait(B+st*8,ph);
      const unsigned sa=sb+WS_STAGE+st*32768;
      const uint64_t da=mkdesc(sa+r*8192,16,1024), db=mkdesc(sa+16384,8192,1024);
      wg_fence();
      #pragma unroll
      for(int k=0;k<4;k++) wg_ss_n128_tb(acc,da+k*2,db+k*128,1);
      wg_commit();
      if(kb>0){ wg_wait<1>(); if(lane==0) mbar_arrive(B+32+((st+3)&3)*8); }
      if(++st==4){ st=0; ph^=1; }
    }
    wg_wait<0>(); if(lane==0) mbar_arrive(B+32+((st+3)&3)*8);
    WPH(trA,1); WPH(trW,17); WPH(trK,33);
    if(t.type!=TK_ATT && ntask>0) mbar_wait(B+80,(ntask-1)&1);
    if(t.type==TK_KV){
      const int row=16*(wi&1)+(lane&7)+8*((lane>>3)&1); const unsigned base=sb+WS_KX+(2*r+(wi>>1))*8192;
      #pragma unroll
      for(int jp=0;jp<8;jp++){ const int j=2*jp; const int eh=j>>3, c=(j&7)+(lane>>4);
        stsm4(base+eh*4096+row*128+((c^(row&7))<<4), pack2(acc[4*j],acc[4*j+1]), pack2(acc[4*j+2],acc[4*j+3]), pack2(acc[4*j+4],acc[4*j+5]), pack2(acc[4*j+6],acc[4*j+7])); }
    } else if(t.type==TK_ATT){
      unsigned qa[8][4];
      #pragma unroll
      for(int k=0;k<8;k++){ qa[k][0]=pack2(acc[8*k],acc[8*k+1]); qa[k][1]=pack2(acc[8*k+2],acc[8*k+3]); qa[k][2]=pack2(acc[8*k+4],acc[8*k+5]); qa[k][3]=pack2(acc[8*k+6],acc[8*k+7]); }
      float sx[32], sm[8];
      mbar_wait(B+64,natt&1);
      WPH(trA,2);
      wg_fence();
      #pragma unroll
      for(int k=0;k<8;k++) wg_rs_n64(sx,qa[k][0],qa[k][1],qa[k][2],qa[k][3],mkdesc(sb+WS_KX+(k>>2)*16384+r*8192+(k&3)*32,16,1024),k!=0);
      wg_commit();
      mbar_wait(B+72,natt&1);
      WPH(trA,3);
      #pragma unroll
      for(int k=0;k<8;k++) wg_rs_n16(sm,qa[k][0],qa[k][1],qa[k][2],qa[k][3],mkdesc(sb+WS_KM+(k>>2)*4096+r*2048+(k&3)*32,16,1024),k!=0);
      wg_commit(); wg_wait<0>();
      WPH(trA,4);
      const bool s1=(wi>>1)!=0; float x[16], mm[4];
      #pragma unroll
      for(int i=0;i<16;i++) x[i]= s1? sx[16+i]: sx[i];
      #pragma unroll
      for(int i=0;i<4;i++) mm[i]= s1? sm[4+i]: sm[i];
      const int rho0=16*(wi&1)+g, rho1=rho0+8; const float NEG=-3.0e38f;
      #pragma unroll
      for(int j=0;j<4;j++){ const int c=8*j+2*tq;
        if(c>rho0) x[4*j]=NEG; if(c+1>rho0) x[4*j+1]=NEG; if(c>rho1) x[4*j+2]=NEG; if(c+1>rho1) x[4*j+3]=NEG; }
      float m0=fmaxf(mm[0],mm[1]), m1=fmaxf(mm[2],mm[3]);
      #pragma unroll
      for(int j=0;j<4;j++){ m0=fmaxf(m0,fmaxf(x[4*j],x[4*j+1])); m1=fmaxf(m1,fmaxf(x[4*j+2],x[4*j+3])); }
      m0=fmaxf(m0,__shfl_xor_sync(~0u,m0,1)); m0=fmaxf(m0,__shfl_xor_sync(~0u,m0,2));
      m1=fmaxf(m1,__shfl_xor_sync(~0u,m1,1)); m1=fmaxf(m1,__shfl_xor_sync(~0u,m1,2));
      const float sl2=0.08838834764831845f*1.4426950408889634f; const float n0=-m0*sl2, n1=-m1*sl2;
      unsigned px[4][2], pm[2]; float l0=0.f,l1=0.f;
      #pragma unroll
      for(int j=0;j<4;j++){ px[j][0]=pack2(ex2(fmaf(x[4*j],sl2,n0)),ex2(fmaf(x[4*j+1],sl2,n0))); px[j][1]=pack2(ex2(fmaf(x[4*j+2],sl2,n1)),ex2(fmaf(x[4*j+3],sl2,n1)));
        l0+=blo(px[j][0])+bhi(px[j][0]); l1+=blo(px[j][1])+bhi(px[j][1]); }
      pm[0]=pack2(ex2(fmaf(mm[0],sl2,n0)),ex2(fmaf(mm[1],sl2,n0))); pm[1]=pack2(ex2(fmaf(mm[2],sl2,n1)),ex2(fmaf(mm[3],sl2,n1)));
      l0+=blo(pm[0])+bhi(pm[0]); l1+=blo(pm[1])+bhi(pm[1]);
      l0+=__shfl_xor_sync(~0u,l0,1); l0+=__shfl_xor_sync(~0u,l0,2); l1+=__shfl_xor_sync(~0u,l1,1); l1+=__shfl_xor_sync(~0u,l1,2);
      WPH(trA,5);
      wg_fence();
      #pragma unroll
      for(int kk=0;kk<4;kk++){ const bool on=((kk>>1)!=0)==s1; const int j=2*(kk&1);
        wg_rs_n128_tb(acc, on?px[j][0]:0u, on?px[j][1]:0u, on?px[j+1][0]:0u, on?px[j+1][1]:0u, mkdesc(sb+WS_VX+r*8192+kk*2048,16384,1024), kk!=0); }
      wg_rs_n128_tb(acc, s1?0u:pm[0], s1?0u:pm[1], s1?pm[0]:0u, s1?pm[1]:0u, mkdesc(sb+WS_VM+r*2048,4096,1024), 1);
      wg_commit(); wg_wait<0>();
      WPH(trA,6);
      const float i0=__fdividef(1.f,l0), i1=__fdividef(1.f,l1);
      #pragma unroll
      for(int j=0;j<16;j++){ acc[4*j]*=i0; acc[4*j+1]*=i0; acc[4*j+2]*=i1; acc[4*j+3]*=i1; }
      stage_tile(acc,sb+WS_KX+r*8192,16384,wi,lane);
      natt++;
    } else {
      if(t.nsplit==1) stage_tile(acc,sb+WS_KX+r*8192,16384,wi,lane);
      else {
        float* pb=g_part+((size_t)((t.m-12)*4+t.n)*8)*16384;
        float* p=pb+(size_t)t.ks*16384+(r*64+16*wi+g)*128+2*tq;
        #pragma unroll
        for(int j=0;j<16;j++){ *(float2*)(p+8*j)=make_float2(acc[4*j],acc[4*j+1]); *(float2*)(p+8*128+8*j)=make_float2(acc[4*j+2],acc[4*j+3]); }
        WPH(trW,18);
        __threadfence(); bar_sync(11,256);
        WPH(trW,19);
        if(w==0&&lane==0){ asm volatile("red.relaxed.gpu.global.add.u32 [%0],1;"::"l"(&g_pcnt[t.m*4+t.n]):"memory"); int gg=0; while((int)(ldg_relaxed(&g_pcnt[t.m*4+t.n])-epoch*t.nsplit)<0 && ++gg<WAIT_LIMIT); }
        bar_sync(11,256);
        WPH(trW,20);
        const int rows=128/t.nsplit, tid=w*32+lane;
        #pragma unroll 2
        for(int i=tid;i<rows*32;i+=256){ const int rr=t.ks*rows+(i>>5), c4=(i&31)*4; float4 v[8];
          #pragma unroll
          for(int k=0;k<8;k++) v[k]= k<t.nsplit? __ldcg((const float4*)(pb+(size_t)k*16384+rr*128+c4)) : make_float4(0,0,0,0);
          float4 s4=v[0];
          #pragma unroll
          for(int k=1;k<8;k++){ s4.x+=v[k].x; s4.y+=v[k].y; s4.z+=v[k].z; s4.w+=v[k].w; }
          uint2 o; o.x=pack2(s4.x,s4.y); o.y=pack2(s4.z,s4.w);
          *(uint2*)(wa.out+(size_t)(t.m*128+rr)*1024+512+t.n*128+c4)=o; }
      }
    }
    WPH(trA,7); WPH(trW,21); WPH(trK,34);
    asm volatile("fence.proxy.async.shared::cta;":::"memory");
    bar_sync(10,288);
    WPH(trA,8); WPH(trW,22); WPH(trK,35);
    ntask++;
  }
}
struct AllArgs { ChainArgs c; ConvArgs cv; WorkArgs w; };
#define SMEM_TOTAL (CS_TOTAL>WS_END?CS_TOTAL:WS_END)
template<int DBG>
__global__ void __launch_bounds__(384,1) fused_kernel(const __grid_constant__ WorkMaps mp, const __grid_constant__ AllArgs a){
  extern __shared__ __align__(1024) unsigned char smem[];
  const unsigned sb=s2u(smem);
  const unsigned epoch=*(volatile unsigned*)&g_epoch+1;
  const int cta=blockIdx.x;
  if(cta<64){
    chain_role<DBG>(a.c,&mp.wo,sb,cta,epoch);
  } else {
    const int tid=threadIdx.x, lane=tid&31; const int w=__shfl_sync(~0u,tid>>5,0); const int wk=cta-64, nw=gridDim.x-64;
    if(tid==0){ const unsigned B=sb+WS_BAR; for(int i=0;i<4;i++){ mbar_init(B+i*8,1); mbar_init(B+32+i*8,8);} mbar_init(B+64,1); mbar_init(B+72,1); mbar_init(B+80,1);
      asm volatile("fence.mbarrier_init.release.cluster;":::"memory"); asm volatile("fence.proxy.async.shared::cta;":::"memory"); }
    __syncthreads();
    if(w>=8){
      reg_dealloc<56>();
      if(w==8) worker_producer(mp,sb,wk,nw,epoch,lane);
      else if(w==9) worker_storer(mp,sb,wk,nw,epoch,lane);
      else if(w==10) worker_aux(sb,wk,nw,epoch,lane);
    } else {
      reg_alloc<224>();
      worker_consumer<DBG>(a.w,a.cv,sb,wk,nw,epoch,w,lane);
    }
  }
  __syncthreads();
  if(threadIdx.x==0){ unsigned o=atomicAdd(&g_done,1); if(o==gridDim.x-1){ g_done=0; *(volatile unsigned*)&g_epoch=epoch; } }
}
typedef CUresult (*EncFn)(CUtensorMap*,CUtensorMapDataType,cuuint32_t,void*,const cuuint64_t*,const cuuint64_t*,const cuuint32_t*,const cuuint32_t*,CUtensorMapInterleave,CUtensorMapSwizzle,CUtensorMapL2promotion,CUtensorMapFloatOOBfill);
static void mkmap(EncFn enc, CUtensorMap* m, const void* p, uint64_t cols, uint64_t rows, uint32_t bc, uint32_t br){
  cuuint64_t gd[2]={cols,rows}; cuuint64_t gs[1]={cols*2}; cuuint32_t box[2]={bc,br}; cuuint32_t es[2]={1,1};
  enc(m,CU_TENSOR_MAP_DATA_TYPE_BFLOAT16,2,(void*)p,gd,gs,box,es,CU_TENSOR_MAP_INTERLEAVE_NONE,CU_TENSOR_MAP_SWIZZLE_128B,CU_TENSOR_MAP_L2_PROMOTION_L2_128B,CU_TENSOR_MAP_FLOAT_OOB_FILL_NONE);
}

extern "C" void kernel_launch(void* const* d_in, const int* in_sizes, int n_in, void* d_out, int out_size) {
  (void)in_sizes; (void)n_in; (void)out_size;
  static EncFn enc = nullptr; static int nclusters = 0; static void* go = nullptr;
  auto kern = fused_kernel<0>;
  cudaLaunchConfig_t cfg = {};
  cfg.blockDim = dim3(384); cfg.dynamicSmemBytes = SMEM_TOTAL; cfg.stream = cudaStreamPerThread;
  cudaLaunchAttribute at[1]; at[0].id = cudaLaunchAttributeClusterDimension; at[0].val.clusterDim.x = 2; at[0].val.clusterDim.y = 1; at[0].val.clusterDim.z = 1;
  cfg.attrs = at; cfg.numAttrs = 1;
  if (!enc) {
    void* fn = nullptr; cudaDriverEntryPointQueryResult qr;
    cudaGetDriverEntryPoint("cuTensorMapEncodeTiled", &fn, cudaEnableDefault, &qr);
    enc = (EncFn)fn;
    cudaFuncSetAttribute(kern, cudaFuncAttributeMaxDynamicSharedMemorySize, SMEM_TOTAL);
    cfg.gridDim = dim3(132);
    cudaOccupancyMaxActiveClusters(&nclusters, kern, &cfg);
    cudaGetSymbolAddress(&go, g_o);
  }
  AllArgs a;
  a.cv.u=(const bf16*)d_in[0]; a.cv.Are=(const bf16*)d_in[1]; a.cv.Aim=(const bf16*)d_in[2]; a.cv.Bre=(const bf16*)d_in[3]; a.cv.Bim=(const bf16*)d_in[4];
  a.cv.Cre=(const bf16*)d_in[5]; a.cv.Cim=(const bf16*)d_in[6]; a.cv.logdt=(const bf16*)d_in[7]; a.cv.Dskip=(const bf16*)d_in[8];
  a.c.x=(const bf16*)d_in[9]; a.c.mem0=(const bf16*)d_in[10]; a.c.Wq=(const bf16*)d_in[11]; a.c.Wk=(const bf16*)d_in[12]; a.c.Wv=(const bf16*)d_in[13]; a.c.Wo=(const bf16*)d_in[14];
  a.c.delay = CHAIN_DELAY; a.c.adapt = 0; a.c.skip = 0;
  a.cv.out=(bf16*)d_out; a.cv.dbgK=nullptr; a.cv.dbgT=0; a.w.out=(bf16*)d_out;
  const int grid = 2*nclusters; a.w.nw = grid-64;
  WorkMaps mp;
  mkmap(enc,&mp.x,a.c.x,512,2048,64,128); mkmap(enc,&mp.wq,a.c.Wq,4096,512,64,64); mkmap(enc,&mp.wk,a.c.Wk,4096,512,64,64); mkmap(enc,&mp.wv,a.c.Wv,4096,512,64,64);
  mkmap(enc,&mp.wo,a.c.Wo,512,4096,64,64); mkmap(enc,&mp.o,go,4096,2048,64,128); mkmap(enc,&mp.o64,go,4096,2048,64,64); mkmap(enc,&mp.out64,d_out,1024,2048,64,64);
  cfg.gridDim = dim3(grid);
  cudaLaunchKernelEx(&cfg, kern, mp, a);
}
```
